```python
import torch

def _softmax(x, axis=-1):
    return torch.softmax(x, dim=axis)
def _gelu(x):
    return torch.nn.functional.gelu(x, approximate="tanh")
def _silu(x):
    return torch.nn.functional.silu(x)
def _sigmoid(x):
    return torch.sigmoid(x)
def _layernorm(x, axis=-1, eps=1e-5):
    m = x.mean(dim=axis, keepdim=True)
    v = x.var(dim=axis, keepdim=True, unbiased=False)
    return (x - m) / torch.sqrt(v + eps)
def _scatter_add(tgt, idx, src, axis=0):
    return tgt.clone().index_add_(axis, idx, src)
def _segment_sum(src, seg, n):
    out = torch.zeros((n,) + src.shape[1:], dtype=src.dtype)
    return out.index_add_(0, seg, src)
def _pad(x, pw):
    flat = tuple(v for pair in reversed(pw) for v in pair)
    return torch.nn.functional.pad(x, flat)

kernel_name = 'gated_mix__ssm_conv_s4d__ssm_conv_s5__prompt'

def setup_inputs():

    _w = (lambda a: (lambda t: t.to(torch.bfloat16) if t.is_floating_point() else t)(torch.as_tensor(a)))
    def _A_setup():
        Bsz, L, D, N = 1, 2048, 448, 256
        return {
            "u": _w((lambda *s: torch.randn(*s, dtype=torch.bfloat16) * 0.05)(Bsz, L, D)),
            "log_A_real": _w((lambda *s: torch.randn(*s, dtype=torch.bfloat16) * 3.2)(D, N) * 0.5),
            "A_imag": _w((lambda *s: torch.randn(*s, dtype=torch.bfloat16) * 0.05)(D, N) * 3.14),
            "C_real": _w((lambda *s: torch.randn(*s, dtype=torch.bfloat16) * 0.1)(D, N) / N ** 0.5),
            "C_imag": _w((lambda *s: torch.randn(*s, dtype=torch.bfloat16) * 0.1)(D, N) / N ** 0.5),
            "log_dt": _w((lambda *s: torch.randn(*s, dtype=torch.bfloat16) * 0.05)(D) * 0.5 - 4.0),
            "D_skip": _w((lambda *s: torch.randn(*s, dtype=torch.bfloat16) * 0.05)(D)),
        }
    _A_in = _A_setup()

    def _B_setup():
        B, S, D = 1, 2048, 448
        P = D
        Lambda_re = -0.5 * (lambda _x: torch.exp(torch.as_tensor(_x)))((lambda *s: torch.randn(*s, dtype=torch.bfloat16) * 0.2)(P))
        Lambda_im = (lambda *s: torch.randn(*s, dtype=torch.bfloat16) * 0.4)(P) * 1.0
        B_re = (lambda *s: torch.randn(*s, dtype=torch.bfloat16) * 0.2)(P, D) * (D ** -0.5)
        B_im = (lambda *s: torch.randn(*s, dtype=torch.bfloat16) * 0.2)(P, D) * (D ** -0.5)
        C_re = (lambda *s: torch.randn(*s, dtype=torch.bfloat16) * 0.2)(D, P) * (P ** -0.5)
        C_im = (lambda *s: torch.randn(*s, dtype=torch.bfloat16) * 0.2)(D, P) * (P ** -0.5)
        log_dt = (lambda *s: torch.randn(*s, dtype=torch.bfloat16) * 0.2)(P) * 0.3 - 2.0
        Dskip = (lambda *s: torch.randn(*s, dtype=torch.bfloat16) * 0.05)(D)
        return {
            "x": _w((lambda *s: torch.randn(*s, dtype=torch.bfloat16) * 0.05)(B, S, D)),
            "Lambda_re": _w(Lambda_re),
            "Lambda_im": _w(Lambda_im),
            "B_re": _w(B_re),
            "B_im": _w(B_im),
            "C_re": _w(C_re),
            "C_im": _w(C_im),
            "log_dt": _w(log_dt),
            "Dskip": _w(Dskip),
        }
    _B_in = _B_setup()

    return {
        "A_u": _A_in["u"],
        "A_log_A_real": _A_in["log_A_real"],
        "A_A_imag": _A_in["A_imag"],
        "A_C_real": _A_in["C_real"],
        "A_C_imag": _A_in["C_imag"],
        "A_log_dt": _A_in["log_dt"],
        "A_D_skip": _A_in["D_skip"],
        "B_x": _B_in["x"],
        "B_Lambda_re": _B_in["Lambda_re"],
        "B_Lambda_im": _B_in["Lambda_im"],
        "B_B_re": _B_in["B_re"],
        "B_B_im": _B_in["B_im"],
        "B_C_re": _B_in["C_re"],
        "B_C_im": _B_in["C_im"],
        "B_log_dt": _B_in["log_dt"],
        "B_Dskip": _B_in["Dskip"],
        "gate_w": _w((lambda *s: torch.randn(*s, dtype=torch.bfloat16) * 0.05)(448) * 16.0),
    }

def reference(A_u, A_log_A_real, A_A_imag, A_C_real, A_C_imag, A_log_dt, A_D_skip, B_x, B_Lambda_re, B_Lambda_im, B_B_re, B_B_im, B_C_re, B_C_im, B_log_dt, B_Dskip, gate_w):
    def _A_ref(u, log_A_real, A_imag, C_real, C_imag, log_dt, D_skip):
        L = u.shape[1]
        dt = torch.exp(log_dt)
        A = -torch.exp(log_A_real) + 1j * A_imag
        C = (C_real + 1j * C_imag) * dt[:, None]
        pos = (lambda x, dt: x.to(dt))(torch.arange(L), log_dt.dtype)
        P = torch.exp((A * dt[:, None])[:, :, None] * pos[None, None, :])
        K = 2.0 * torch.einsum("dn,dnl->dl", C, P).real
        L2 = 2 * L
        u_t = (lambda x, *d: x.permute(*d))(u, 0, 2, 1)
        Kf = (lambda x, *a, **k: torch.fft.rfft(x.float(), *a, **k))(K, L2)
        Uf = (lambda x, *a, **k: torch.fft.rfft(x.float(), *a, **k))(u_t, L2)
        y = (lambda x, *a, **k: torch.fft.irfft(x, *a, **k).to(torch.bfloat16))(Uf * Kf[None, :, :], L2)[:, :, :L]
        y = (lambda x, *d: x.permute(*d))(y, 0, 2, 1)
        return y + u * D_skip[None, None, :]

    def _B_ref(x, Lambda_re, Lambda_im, B_re, B_im, C_re, C_im, log_dt, Dskip):
        Bsz, L, H = x.shape
        Lam = Lambda_re + 1j * Lambda_im
        Bmat = B_re + 1j * B_im
        Cmat = C_re + 1j * C_im
        dt = torch.exp(log_dt)
        Lam_bar = torch.exp(dt * Lam)
        B_bar = ((Lam_bar - 1.0) / Lam)[:, None] * Bmat
        Bu = torch.einsum("bld,pd->blp", x + 0j, B_bar)
        h = torch.zeros_like(Bu[:, 0, :])
        hs = []
        for t in range(L):
            h = Lam_bar[None, :] * h + Bu[:, t, :]
            hs.append(h)
        hseq = torch.stack(hs, 1)
        y = 2.0 * torch.einsum("blp,dp->bld", hseq, Cmat).real + x * Dskip[None, None, :]
        return y

    x = A_u
    g = _sigmoid((x * gate_w).sum(-1, keepdims=True))
    a = _A_ref(x, A_log_A_real, A_A_imag, A_C_real, A_C_imag, A_log_dt, A_D_skip)
    b = _B_ref(x, B_Lambda_re, B_Lambda_im, B_B_re, B_B_im, B_C_re, B_C_im, B_log_dt, B_Dskip)
    return g * a + (1 - g) * b
```

```cpp
#include <cuda_runtime.h>
#include <cuda.h>
#include <cuda_bf16.h>
#include <cuda_fp16.h>
#include <stdint.h>
#include <stddef.h>

namespace {

constexpr int L_ = 2048, D_ = 448;
constexpr int NS5 = 112;
constexpr int NTHREADS = 640;
constexpr int MAXCTA = 132;

constexpr uint32_t SB = 1024;
constexpr int SLOT = 16384;
constexpr int OFF_XOWN = 7 * SLOT;
constexpr int S4D_SZ = 32768;
constexpr int OFF_BAR = 14 * SLOT;
constexpr int OFF_G = OFF_BAR + 512;
constexpr int OFF_GW = OFF_G + 512;
constexpr int SMEM_BYTES = OFF_GW + 1024;
constexpr uint32_t XSLOT = 0x2642642;
constexpr uint32_t HSLOT = 0x0b70b7b, CSLOT = 0x2654321;
constexpr int B_FULL1 = 0, B_XO = 7, B_GA = 8, B_G1 = 9, B_OWN = 10, B_FULL2 = 11, B_KG = 18, B_U = 19, B_CNT = 24;
constexpr int R_F2 = 0, R_F3 = 3072, R_FAR = 3072, R_K0 = 5120, R_LIN = 5248, R_NEAR = 8944, R_U = 12288;
constexpr int FARW = 84;

struct __align__(128) Scratch {
    uint32_t epoch[MAXCTA * 24];
    uint32_t flag[NS5 * 32];
    uint32_t flagA[D_];
    uint2 agg[NS5 * 64];
    uint32_t gpart[NS5 * 128];
    uint4 uT[D_ * L_ / 8];
    uint4 aT[D_ * L_ / 8];
    uint4 h[NS5 * 2 * 1024];
};
__device__ Scratch g_scr;
#define TS(i)
#define TSDUMP()
#define TSG(i)

struct Params {
    CUtensorMap mx, mb, mc, ma, mu, ms;
    const uint32_t *logA, *Aim, *Cre, *Cim;
    const uint16_t *logdtA, *DA, *Lre, *Lim, *logdtB, *DB, *gw;
    const char *Cr, *Ci;
    float* out;
    int nextra, nwg, swapB, swapC;
    uint32_t zero;
};

__device__ __forceinline__ float bflo(uint32_t v) { return __uint_as_float(v << 16); }
__device__ __forceinline__ float bfhi(uint32_t v) { return __uint_as_float(v & 0xffff0000u); }
__device__ __forceinline__ uint32_t ldg32(const void* p) {
    uint32_t v; asm volatile("ld.global.nc.u32 %0, [%1];" : "=r"(v) : "l"(p)); return v;
}
__device__ __forceinline__ float bf1(const uint16_t* p) {
    uint32_t v; asm volatile("ld.global.nc.u16 %0, [%1];" : "=r"(v) : "l"(p)); return __uint_as_float(v << 16);
}
__device__ __forceinline__ uint32_t packbf(float lo, float hi) {
    uint32_t r; asm("cvt.rn.bf16x2.f32 %0, %1, %2;" : "=r"(r) : "f"(hi), "f"(lo)); return r;
}
__device__ __forceinline__ uint32_t packh(float lo, float hi) {
    uint32_t r; asm("cvt.rn.f16x2.f32 %0, %1, %2;" : "=r"(r) : "f"(hi), "f"(lo)); return r;
}
__device__ __forceinline__ float bfround(float x) { return bflo(packbf(x, 0.f)); }
__device__ __forceinline__ float ex2(float x) { float r; asm("ex2.approx.ftz.f32 %0, %1;" : "=f"(r) : "f"(x)); return r; }
__device__ __forceinline__ float fsin(float x) { float r; asm("sin.approx.ftz.f32 %0, %1;" : "=f"(r) : "f"(x)); return r; }
__device__ __forceinline__ float fcos(float x) { float r; asm("cos.approx.ftz.f32 %0, %1;" : "=f"(r) : "f"(x)); return r; }
__device__ __forceinline__ float frcp(float x) { float r; asm("rcp.approx.ftz.f32 %0, %1;" : "=f"(r) : "f"(x)); return r; }
constexpr float LOG2E = 1.4426950408889634f;

struct C2 { __half2 r, i; };
__device__ __forceinline__ C2 cmul(C2 a, C2 b) {
    return C2{__hfma2(a.r, b.r, __hneg2(__hmul2(a.i, b.i))), __hfma2(a.r, b.i, __hmul2(a.i, b.r))};
}
__device__ __forceinline__ C2 cmulc(C2 a, C2 b) {
    return C2{__hfma2(a.r, b.r, __hmul2(a.i, b.i)), __hfma2(a.i, b.r, __hneg2(__hmul2(a.r, b.i)))};
}
__device__ __forceinline__ uint32_t hb(__half2 v) { return *reinterpret_cast<uint32_t*>(&v); }
__device__ __forceinline__ __half2 bh(uint32_t v) { return *reinterpret_cast<__half2*>(&v); }
__device__ __forceinline__ uint32_t mulbf2(uint32_t a, uint32_t b) {
    uint32_t r; asm volatile("mul.rn.bf16x2 %0, %1, %2;" : "=r"(r) : "r"(a), "r"(b)); return r;
}

#define EL "{\n.reg .pred q;\nelect.sync _|q, 0xffffffff;\n@q "
__device__ __forceinline__ void mbar_init(uint32_t bar, int cnt) {
    asm volatile(EL "mbarrier.init.shared::cta.b64 [%0], %1;\n}" ::"r"(bar), "r"(cnt) : "memory");
}
__device__ __forceinline__ void mbar_expect(uint32_t bar, uint32_t bytes) {
    asm volatile(EL "mbarrier.arrive.expect_tx.shared::cta.b64 _, [%0], %1;\n}" ::"r"(bar), "r"(bytes) : "memory");
}
__device__ __forceinline__ void mbar_arrive(uint32_t bar) {
    asm volatile(EL "mbarrier.arrive.shared::cta.b64 _, [%0];\n}" ::"r"(bar) : "memory");
}
__device__ __forceinline__ bool second_arrival(uint32_t a) {
    uint32_t v = 0;
    asm volatile(EL "atom.relaxed.cta.shared.exch.b32 %0, [%1], 1;\n}" : "+r"(v) : "r"(a) : "memory");
    return __any_sync(0xffffffffu, v != 0);
}
__device__ __forceinline__ void mbar_wait(uint32_t bar, uint32_t par) {
    asm volatile(
        "{\n.reg .pred p;\n.reg .u32 n;\nmov.u32 n, 0;\n"
        "W%=:\nmbarrier.try_wait.parity.shared::cta.b64 p, [%0], %1;\n@p bra D%=;\n"
        "add.u32 n, n, 1;\nsetp.lt.u32 p, n, 0x80000;\n@p bra W%=;\ntrap;\nD%=:\n}" ::"r"(bar), "r"(par) : "memory");
}
constexpr int POLL_LIMIT = 1 << 20;
__device__ __forceinline__ void bar_sync(int id, int n) { asm volatile("bar.sync %0, %1;" ::"r"(id), "r"(n) : "memory"); }
__device__ __forceinline__ void fence_async_smem() { asm volatile("fence.proxy.async.shared::cta;" ::: "memory"); }
__device__ __forceinline__ void fence_async_glob() { asm volatile("fence.proxy.async.global;" ::: "memory"); }
__device__ __forceinline__ void tma2(uint32_t dst, const CUtensorMap* m, int c0, int c1, uint32_t bar) {
    asm volatile(EL "cp.async.bulk.tensor.2d.shared::cluster.global.mbarrier::complete_tx::bytes [%0], [%1, {%3, %4}], [%2];\n}"
                 ::"r"(dst), "l"(m), "r"(bar), "r"(c0), "r"(c1) : "memory");
}
__device__ __forceinline__ void tma4(uint32_t dst, const CUtensorMap* m, int c0, int c3, uint32_t bar) {
    asm volatile(EL "cp.async.bulk.tensor.4d.shared::cluster.global.mbarrier::complete_tx::bytes [%0], [%1, {%3, %5, %5, %4}], [%2];\n}"
                 ::"r"(dst), "l"(m), "r"(bar), "r"(c0), "r"(c3), "r"(0) : "memory");
}
__device__ __forceinline__ void tma5(uint32_t dst, const CUtensorMap* m, int c0, int c3, int c4, uint32_t bar) {
    asm volatile(EL "cp.async.bulk.tensor.5d.shared::cluster.global.mbarrier::complete_tx::bytes [%0], [%1, {%3, %6, %6, %4, %5}], [%2];\n}"
                 ::"r"(dst), "l"(m), "r"(bar), "r"(c0), "r"(c3), "r"(c4), "r"(0) : "memory");
}
__device__ __forceinline__ void bulk_ld(uint32_t dst, const void* src, uint32_t n, uint32_t bar) {
    asm volatile(EL "cp.async.bulk.shared::cluster.global.mbarrier::complete_tx::bytes [%0], [%1], %2, [%3];\n}"
                 ::"r"(dst), "l"(src), "r"(n), "r"(bar) : "memory");
}
__device__ __forceinline__ void bulk_wait() { asm volatile("cp.async.bulk.wait_group 0;" ::: "memory"); __syncwarp(); }
__device__ __forceinline__ void bulk_st(void* dst, uint32_t src, uint32_t n) {
    asm volatile(EL "cp.async.bulk.global.shared::cta.bulk_group [%0], [%1], %2;\n}\ncp.async.bulk.commit_group;" ::"l"(dst), "r"(src), "r"(n) : "memory");
}
__device__ __forceinline__ void st_flag(uint32_t* p, uint32_t v) {
    asm volatile("st.relaxed.gpu.global.u32 [%0], %1;" ::"l"(p), "r"(v) : "memory");
}
__device__ __forceinline__ uint32_t ld_flag(const uint32_t* p) {
    uint32_t v; asm volatile("ld.relaxed.gpu.global.u32 %0, [%1];" : "=r"(v) : "l"(p) : "memory"); return v;
}
__device__ __forceinline__ uint2 ld_flag2(const void* p) {
    uint2 v; asm volatile("ld.relaxed.gpu.global.v2.u32 {%0,%1}, [%2];" : "=r"(v.x), "=r"(v.y) : "l"(p) : "memory"); return v;
}
__device__ __forceinline__ uint4 ld_flag4(const void* p) {
    uint4 v; asm volatile("ld.relaxed.gpu.global.v4.u32 {%0,%1,%2,%3}, [%4];" : "=r"(v.x), "=r"(v.y), "=r"(v.z), "=r"(v.w) : "l"(p) : "memory"); return v;
}
__device__ __forceinline__ uint32_t lds32(uint32_t a) { uint32_t v; asm volatile("ld.shared.u32 %0, [%1];" : "=r"(v) : "r"(a) : "memory"); return v; }
__device__ __forceinline__ uint32_t lds16(uint32_t a) { uint16_t v; asm volatile("ld.shared.u16 %0, [%1];" : "=h"(v) : "r"(a) : "memory"); return v; }
__device__ __forceinline__ uint4 lds128(uint32_t a) {
    uint4 v; asm volatile("ld.shared.v4.u32 {%0,%1,%2,%3}, [%4];" : "=r"(v.x), "=r"(v.y), "=r"(v.z), "=r"(v.w) : "r"(a) : "memory"); return v;
}
__device__ __forceinline__ void sts16(uint32_t a, uint32_t v) { asm volatile("st.shared.u16 [%0], %1;" ::"r"(a), "h"((uint16_t)v) : "memory"); }
__device__ __forceinline__ void sts32(uint32_t a, uint32_t v) { asm volatile("st.shared.u32 [%0], %1;" ::"r"(a), "r"(v) : "memory"); }
__device__ __forceinline__ void sts128(uint32_t a, uint32_t x, uint32_t y, uint32_t z, uint32_t w) {
    asm volatile("st.shared.v4.u32 [%0], {%1,%2,%3,%4};" ::"r"(a), "r"(x), "r"(y), "r"(z), "r"(w) : "memory");
}
__device__ __forceinline__ void sts64(uint32_t a, uint32_t x, uint32_t y) {
    asm volatile("st.shared.v2.u32 [%0], {%1,%2};" ::"r"(a), "r"(x), "r"(y) : "memory");
}
__device__ __forceinline__ uint2 ldsm2t(uint32_t a) {
    uint2 v; asm volatile("ldmatrix.sync.aligned.m8n8.x2.trans.shared.b16 {%0,%1}, [%2];" : "=r"(v.x), "=r"(v.y) : "r"(a) : "memory"); return v;
}
__device__ __forceinline__ void stsm2(uint32_t a, uint32_t x, uint32_t y) {
    asm volatile("stmatrix.sync.aligned.m8n8.x2.shared.b16 [%0], {%1,%2};" ::"r"(a), "r"(x), "r"(y) : "memory");
}
__device__ __forceinline__ bool mbar_test(uint32_t bar) {
    uint32_t p;
    asm volatile("{\n.reg .pred q;\nmbarrier.test_wait.parity.shared::cta.b64 q, [%1], 0;\nselp.u32 %0, 1, 0, q;\n}" : "=r"(p) : "r"(bar) : "memory");
    return p != 0;
}
__device__ __forceinline__ uint4 ldsm4(uint32_t a) {
    uint4 v; asm volatile("ldmatrix.sync.aligned.m8n8.x4.shared.b16 {%0,%1,%2,%3}, [%4];" : "=r"(v.x), "=r"(v.y), "=r"(v.z), "=r"(v.w) : "r"(a) : "memory"); return v;
}
__device__ __forceinline__ uint4 ldsm4t(uint32_t a) {
    uint4 v; asm volatile("ldmatrix.sync.aligned.m8n8.x4.trans.shared.b16 {%0,%1,%2,%3}, [%4];" : "=r"(v.x), "=r"(v.y), "=r"(v.z), "=r"(v.w) : "r"(a) : "memory"); return v;
}
__device__ __forceinline__ void stsm4(uint32_t a, uint32_t x, uint32_t y, uint32_t z, uint32_t w) {
    asm volatile("stmatrix.sync.aligned.m8n8.x4.shared.b16 [%0], {%1,%2,%3,%4};" ::"r"(a), "r"(x), "r"(y), "r"(z), "r"(w) : "memory");
}
__device__ __forceinline__ void stsm4t(uint32_t a, uint32_t x, uint32_t y, uint32_t z, uint32_t w) {
    asm volatile("stmatrix.sync.aligned.m8n8.x4.trans.shared.b16 [%0], {%1,%2,%3,%4};" ::"r"(a), "r"(x), "r"(y), "r"(z), "r"(w) : "memory");
}
__device__ __forceinline__ void mma_f16(float (&d)[4], uint32_t a0, uint32_t a1, uint32_t a2, uint32_t a3, uint32_t b0, uint32_t b1) {
    asm volatile("mma.sync.aligned.m16n8k16.row.col.f32.f16.f16.f32 {%0,%1,%2,%3},{%4,%5,%6,%7},{%8,%9},{%0,%1,%2,%3};"
                 : "+f"(d[0]), "+f"(d[1]), "+f"(d[2]), "+f"(d[3]) : "r"(a0), "r"(a1), "r"(a2), "r"(a3), "r"(b0), "r"(b1));
}
__device__ __forceinline__ void mma_bf16(float (&d)[4], uint4 a, uint32_t b0, uint32_t b1) {
    asm volatile("mma.sync.aligned.m16n8k16.row.col.f32.bf16.bf16.f32 {%0,%1,%2,%3},{%4,%5,%6,%7},{%8,%9},{%0,%1,%2,%3};"
                 : "+f"(d[0]), "+f"(d[1]), "+f"(d[2]), "+f"(d[3]) : "r"(a.x), "r"(a.y), "r"(a.z), "r"(a.w), "r"(b0), "r"(b1));
}
__device__ __forceinline__ void mma_bf16_z(float (&d)[4], uint4 a, uint32_t b0, uint32_t b1) {
    asm volatile("mma.sync.aligned.m16n8k16.row.col.f32.bf16.bf16.f32 {%0,%1,%2,%3},{%4,%5,%6,%7},{%8,%9},{%10,%10,%10,%10};"
                 : "=f"(d[0]), "=f"(d[1]), "=f"(d[2]), "=f"(d[3]) : "r"(a.x), "r"(a.y), "r"(a.z), "r"(a.w), "r"(b0), "r"(b1), "f"(0.f));
}
__device__ __forceinline__ void mma_bf16_c(float (&d)[4], const uint32_t (&a)[4], uint32_t b0, uint32_t b1, const float (&c)[4]) {
    asm volatile("mma.sync.aligned.m16n8k16.row.col.f32.bf16.bf16.f32 {%0,%1,%2,%3},{%4,%5,%6,%7},{%8,%9},{%10,%11,%12,%13};"
                 : "=f"(d[0]), "=f"(d[1]), "=f"(d[2]), "=f"(d[3])
                 : "r"(a[0]), "r"(a[1]), "r"(a[2]), "r"(a[3]), "r"(b0), "r"(b1), "f"(c[0]), "f"(c[1]), "f"(c[2]), "f"(c[3]));
}
__device__ __forceinline__ void far_apply(float (&o)[4], float (&c)[4][4], const uint32_t (&T)[2][5][4], uint32_t p0, uint32_t p1,
                                          uint32_t q0, uint32_t q1, uint32_t m) {
    asm volatile("{\n.reg .pred p1, p2, p3, p4;\n.reg .b32 r;\n"
                 "and.b32 r, %64, 2;\nsetp.ne.u32 p1, r, 0;\n"
                 "and.b32 r, %64, 4;\nsetp.ne.u32 p2, r, 0;\n"
                 "and.b32 r, %64, 8;\nsetp.ne.u32 p3, r, 0;\n"
                 "and.b32 r, %64, 16;\nsetp.ne.u32 p4, r, 0;\n"
                 "mma.sync.aligned.m16n8k16.row.col.f32.bf16.bf16.f32 {%0,%1,%2,%3},{%20,%21,%22,%23},{%60,%61},{%4,%5,%6,%7};\n"
                 "@p1 mma.sync.aligned.m16n8k16.row.col.f32.bf16.bf16.f32 {%4,%5,%6,%7},{%24,%25,%26,%27},{%60,%61},{%8,%9,%10,%11};\n"
                 "@p2 mma.sync.aligned.m16n8k16.row.col.f32.bf16.bf16.f32 {%8,%9,%10,%11},{%28,%29,%30,%31},{%60,%61},{%12,%13,%14,%15};\n"
                 "@p3 mma.sync.aligned.m16n8k16.row.col.f32.bf16.bf16.f32 {%12,%13,%14,%15},{%32,%33,%34,%35},{%60,%61},{%16,%17,%18,%19};\n"
                 "@p4 mma.sync.aligned.m16n8k16.row.col.f32.bf16.bf16.f32 {%16,%17,%18,%19},{%36,%37,%38,%39},{%60,%61},{%65,%65,%65,%65};\n"
                 "mma.sync.aligned.m16n8k16.row.col.f32.bf16.bf16.f32 {%0,%1,%2,%3},{%40,%41,%42,%43},{%62,%63},{%0,%1,%2,%3};\n"
                 "@p1 mma.sync.aligned.m16n8k16.row.col.f32.bf16.bf16.f32 {%4,%5,%6,%7},{%44,%45,%46,%47},{%62,%63},{%4,%5,%6,%7};\n"
                 "@p2 mma.sync.aligned.m16n8k16.row.col.f32.bf16.bf16.f32 {%8,%9,%10,%11},{%48,%49,%50,%51},{%62,%63},{%8,%9,%10,%11};\n"
                 "@p3 mma.sync.aligned.m16n8k16.row.col.f32.bf16.bf16.f32 {%12,%13,%14,%15},{%52,%53,%54,%55},{%62,%63},{%12,%13,%14,%15};\n"
                 "@p4 mma.sync.aligned.m16n8k16.row.col.f32.bf16.bf16.f32 {%16,%17,%18,%19},{%56,%57,%58,%59},{%62,%63},{%16,%17,%18,%19};\n"
                 "}"
                 : "=&f"(o[0]), "=&f"(o[1]), "=&f"(o[2]), "=&f"(o[3]),
                   "+f"(c[0][0]), "+f"(c[0][1]), "+f"(c[0][2]), "+f"(c[0][3]), "+f"(c[1][0]), "+f"(c[1][1]), "+f"(c[1][2]), "+f"(c[1][3]),
                   "+f"(c[2][0]), "+f"(c[2][1]), "+f"(c[2][2]), "+f"(c[2][3]), "+f"(c[3][0]), "+f"(c[3][1]), "+f"(c[3][2]), "+f"(c[3][3])
                 : "r"(T[0][0][0]), "r"(T[0][0][1]), "r"(T[0][0][2]), "r"(T[0][0][3]), "r"(T[0][1][0]), "r"(T[0][1][1]), "r"(T[0][1][2]), "r"(T[0][1][3]), "r"(T[0][2][0]), "r"(T[0][2][1]), "r"(T[0][2][2]), "r"(T[0][2][3]), "r"(T[0][3][0]), "r"(T[0][3][1]), "r"(T[0][3][2]), "r"(T[0][3][3]), "r"(T[0][4][0]), "r"(T[0][4][1]), "r"(T[0][4][2]), "r"(T[0][4][3]), "r"(T[1][0][0]), "r"(T[1][0][1]), "r"(T[1][0][2]), "r"(T[1][0][3]), "r"(T[1][1][0]), "r"(T[1][1][1]), "r"(T[1][1][2]), "r"(T[1][1][3]), "r"(T[1][2][0]), "r"(T[1][2][1]), "r"(T[1][2][2]), "r"(T[1][2][3]), "r"(T[1][3][0]), "r"(T[1][3][1]), "r"(T[1][3][2]), "r"(T[1][3][3]), "r"(T[1][4][0]), "r"(T[1][4][1]), "r"(T[1][4][2]), "r"(T[1][4][3]),
                   "r"(p0), "r"(p1), "r"(q0), "r"(q1), "r"(m), "f"(0.f));
}
__device__ __forceinline__ void mma_bf16_k8(float (&d)[4], uint32_t a0, uint32_t a1, uint32_t b0) {
    asm volatile("mma.sync.aligned.m16n8k8.row.col.f32.bf16.bf16.f32 {%0,%1,%2,%3},{%4,%5},{%6},{%0,%1,%2,%3};"
                 : "+f"(d[0]), "+f"(d[1]), "+f"(d[2]), "+f"(d[3]) : "r"(a0), "r"(a1), "r"(b0));
}
__host__ __device__ constexpr uint32_t bandm(int lo, int hi, int c) {
    uint32_t m = 0;
    for (int s = 0; s < 14; s++) {
        const int j = s - 6 + 8 * c;
        if (j >= lo && j <= hi) m |= 1u << (14 - s);
        if (j - 1 >= lo && j - 1 <= hi) m |= 1u << (30 - s);
    }
    return m;
}
__device__ __forceinline__ uint64_t mkdesc(uint32_t addr, uint32_t lbo, uint32_t sbo, uint32_t swz) {
    uint32_t lo = (addr >> 4) | ((lbo >> 4) << 16), hi = (sbo >> 4) | (swz << 30);
    return ((uint64_t)hi << 32) | lo;
}
__device__ __forceinline__ uint64_t desc(uint32_t lo, uint32_t hi) { return ((uint64_t)hi << 32) | lo; }
constexpr uint32_t HI128 = 0x40000040u;
#define WG_FENCE() asm volatile("wgmma.fence.sync.aligned;" ::: "memory")
#define WG_COMMIT() asm volatile("wgmma.commit_group.sync.aligned;" ::: "memory")
#define WG_WAIT(n) asm volatile("wgmma.wait_group.sync.aligned " #n ";" ::: "memory")

template <int N>
__device__ __forceinline__ void pin(float (&d)[N]) {
#pragma unroll
    for (int i = 0; i < N; i++) asm volatile("" : "+f"(d[i])::"memory");
}
#define F4(d, o) "+f"(d[(o)]), "+f"(d[(o) + 1]), "+f"(d[(o) + 2]), "+f"(d[(o) + 3])
#define F8(d, o) F4(d, o), F4(d, (o) + 4)
#define F16(d, o) F8(d, o), F8(d, (o) + 8)
#define F32(d, o) F16(d, o), F16(d, (o) + 16)

__device__ __forceinline__ void wgmma_n128(float (&d)[64], uint64_t da, uint64_t db, int sd) {
    asm volatile("{\n.reg .pred p;\nsetp.ne.b32 p, %66, 0;\n"
        "wgmma.mma_async.sync.aligned.m64n128k16.f32.bf16.bf16 {%0,%1,%2,%3,%4,%5,%6,%7,%8,%9,%10,%11,%12,%13,%14,%15,"
        "%16,%17,%18,%19,%20,%21,%22,%23,%24,%25,%26,%27,%28,%29,%30,%31,%32,%33,%34,%35,%36,%37,%38,%39,%40,%41,%42,%43,%44,%45,%46,%47,"
        "%48,%49,%50,%51,%52,%53,%54,%55,%56,%57,%58,%59,%60,%61,%62,%63}, %64, %65, p, 1, 1, 0, 0;\n}\n"
        : F32(d, 0), F32(d, 32) : "l"(da), "l"(db), "r"(sd));
}
__device__ __forceinline__ void wgmma_n8(float (&d)[4], uint64_t da, uint64_t db, int sd) {
    asm volatile("{\n.reg .pred p;\nsetp.ne.b32 p, %6, 0;\n"
        "wgmma.mma_async.sync.aligned.m64n8k16.f32.bf16.bf16 {%0,%1,%2,%3}, %4, %5, p, 1, 1, 0, 0;\n}\n"
        : F4(d, 0) : "l"(da), "l"(db), "r"(sd));
}
__device__ __forceinline__ void wgmma_n64_tb(float (&d)[32], uint64_t da, uint64_t db) {
    asm volatile("{\n.reg .pred p;\nsetp.eq.b32 p, 0, 0;\n"
        "wgmma.mma_async.sync.aligned.m64n64k16.f32.bf16.bf16 {%0,%1,%2,%3,%4,%5,%6,%7,%8,%9,%10,%11,%12,%13,%14,%15,"
        "%16,%17,%18,%19,%20,%21,%22,%23,%24,%25,%26,%27,%28,%29,%30,%31}, %32, %33, p, 1, 1, 0, 1;\n}\n"
        : F32(d, 0) : "l"(da), "l"(db));
}
__device__ __forceinline__ void wgmma_rs32(float (&d)[16], const uint32_t (&a)[4], uint64_t db) {
    asm volatile("{\n.reg .pred p;\nsetp.eq.b32 p, 0, 0;\n"
        "wgmma.mma_async.sync.aligned.m64n32k16.f32.bf16.bf16 {%0,%1,%2,%3,%4,%5,%6,%7,%8,%9,%10,%11,%12,%13,%14,%15},"
        " {%16,%17,%18,%19}, %20, p, 1, 1, 0;\n}\n"
        : F16(d, 0) : "r"(a[0]), "r"(a[1]), "r"(a[2]), "r"(a[3]), "l"(db));
}
template <int O, int N>
__device__ __forceinline__ void wgmma_rs16_tb(float (&d)[N], const uint32_t (&a)[4], uint64_t db) {
    asm volatile("{\n.reg .pred p;\nsetp.eq.b32 p, 0, 0;\n"
        "wgmma.mma_async.sync.aligned.m64n16k16.f32.bf16.bf16 {%0,%1,%2,%3,%4,%5,%6,%7},"
        " {%8,%9,%10,%11}, %12, p, 1, 1, 1;\n}\n"
        : F8(d, O) : "r"(a[0]), "r"(a[1]), "r"(a[2]), "r"(a[3]), "l"(db));
}
__device__ __forceinline__ void wgmma_rs24_tb(float (&d)[12], const uint32_t (&a)[4], uint64_t db) {
    asm volatile("{\n.reg .pred p;\nsetp.eq.b32 p, 0, 0;\n"
        "wgmma.mma_async.sync.aligned.m64n24k16.f32.bf16.bf16 {%0,%1,%2,%3,%4,%5,%6,%7,%8,%9,%10,%11},"
        " {%12,%13,%14,%15}, %16, p, 1, 1, 1;\n}\n"
        : F4(d, 0), F8(d, 4) : "r"(a[0]), "r"(a[1]), "r"(a[2]), "r"(a[3]), "l"(db));
}
template <int N>
__device__ __forceinline__ void load_toep(uint32_t (*a)[4], uint32_t ta, uint32_t z) {
    a[0][2] = lds32(ta);
#pragma unroll
    for (int i = 0; i < N; i++) {
        a[i][0] = lds32(ta + (2 * i + 1) * 32);
        a[i][1] = lds32(ta + (2 * i + 2) * 32);
    }
#pragma unroll
    for (int i = 0; i < N; i++) {
        a[i][3] = a[i][0] | z;
        if (i) a[i][2] = a[i - 1][1] | z;
    }
}

__device__ __forceinline__ void s4d_channel(const Params& P, int ch, uint32_t R0, uint32_t R, int cload, int pj, bool s5cta, uint32_t ubar, uint32_t uphase,
                                            int barid, uint32_t epoch, uint32_t lar2, uint32_t aim2, uint32_t cr2,
                                            uint32_t ci2, float logdt, float dskip, int w, int role, int tid) {
    const int lane = tid & 31, g = lane >> 2, t = lane & 3;
    const float dt = bfround(ex2(logdt * LOG2E));
    uint32_t cm = __vmaxu2(cr2 & 0x7fff7fffu, ci2 & 0x7fff7fffu);
    cm = __reduce_max_sync(0xffffffffu, max(cm, cm << 16)) & 0x7f800000u;
    const float sc = __uint_as_float(0x7f000000u - cm);
    float k0 = bflo(cr2) + bfhi(cr2);
#pragma unroll
    for (int o = 16; o; o >>= 1) k0 += __shfl_xor_sync(0xffffffffu, k0, o);

    const uint32_t RP = 2 * R0 + SLOT - R;
    const uint32_t stg = R0 + w * 8192, z = P.zero;
    C2 w64;
    {
        const float dl = dt * LOG2E;
        const float r0 = ex2(-bfround(ex2(bflo(lar2) * LOG2E)) * dl), r1 = ex2(-bfround(ex2(bfhi(lar2) * LOG2E)) * dl);
        const float z0 = bflo(aim2) * dt, z1 = bfhi(aim2) * dt;
        float x0 = r0 * fcos(z0), y0 = r0 * fsin(z0), x1 = r1 * fcos(z1), y1 = r1 * fsin(z1);
#define PK() C2{bh(packh(x0, x1)), bh(packh(y0, y1))}
#define SQ() { float t0 = y0 * y0, u0 = x0 + x0, t1 = y1 * y1, u1 = x1 + x1; \
               x0 = fmaf(x0, x0, -t0); y0 = u0 * y0; x1 = fmaf(x1, x1, -t1); y1 = u1 * y1; }
        const C2 G0 = C2{bh(packh(bflo(cr2) * sc, bfhi(cr2) * sc)), bh(packh(bflo(ci2) * -sc, bfhi(ci2) * -sc))};
        const C2 b1 = PK(); SQ();
        const C2 b2 = PK(); SQ();
        const C2 b4 = PK(); SQ();
        const C2 b8 = PK(); SQ();
        const C2 w16 = PK(); SQ();
        const C2 w32 = PK(); SQ();
        w64 = PK(); SQ();
        const C2 w128 = PK(); SQ();
        const C2 w256 = PK(); SQ();
        const C2 w512 = PK(); SQ();
        const C2 e0 = cmul(b8, PK());
        const uint32_t my = stg + lane * 256, sw = ((lane & 1) | ((lane >> 1) & 2) | ((lane & 2) << 1)) << 4;
#define ST(c, a, b) { const C2 a_ = (a), b_ = (b); sts128(my + (((c) * 16) ^ sw), hb(a_.r), hb(a_.i), hb(b_.r), hb(b_.i)); }
        const C2 b3 = cmul(b1, b2), b6 = cmul(b2, b4), c4 = cmul(b4, w512), c5 = cmul(b8, w512);
        ST(0, b1, cmul(b2, w256)); ST(2, b2, cmul(b4, w256)); ST(4, b3, cmul(b6, w256)); ST(6, b4, cmul(b8, w256));
        ST(8, cmul(b1, b4), c4); ST(10, b6, c5); ST(12, cmul(b3, b4), cmul(c4, w256)); ST(14, b8, cmul(c5, w256));
        const C2 G1 = cmulc(G0, b8), G2 = cmulc(G0, w16), G3 = cmulc(G1, w16);
        const C2 e1 = cmul(e0, w128), e2 = cmul(e0, w256), e3 = cmul(e1, w256);
        ST(1, e0, G0); ST(3, e1, G1); ST(5, e2, G2); ST(7, e3, G3);
        ST(9, cmul(e0, w512), cmulc(G0, w32)); ST(11, cmul(e1, w512), cmulc(G1, w32));
        ST(13, cmul(e2, w512), cmulc(G2, w32)); ST(15, cmul(e3, w512), cmulc(G3, w32));
    }
    __syncwarp();
    const uint32_t* fp = &g_scr.flag[((lane >> 1) * 7 + (ch >> 6)) * 32 + (lane & 1) * 4];
    uint4 fv = make_uint4(0u, 0u, 0u, 0u);
    float acc[5][4];
#pragma unroll
    for (int i = 0; i < 5; i++) { acc[i][0] = acc[i][1] = acc[i][2] = acc[i][3] = 0.f; }
    {
        uint32_t a = stg + t * 256 + ((g * 32) ^ (((t & 1) | ((t & 2) << 1)) << 4));
#pragma unroll 1
        for (int ks = 0; ks < 8; ks += 2, a += 2048) {
            if (w == 3 && ks == 4) fv = ld_flag4(fp);
#pragma unroll
            for (int h = 0; h < 2; h++) {
                const uint4 u = lds128((a ^ (h * 32)) + h * 1024), v = lds128((a ^ (h * 32 + 16)) + h * 1024);
                const int src = 4 * (ks + h) + t;
                const C2 m = C2{bh(__shfl_sync(0xffffffffu, hb(w64.r), src)), bh(__shfl_sync(0xffffffffu, hb(w64.i), src))};
                const C2 A0 = C2{bh(v.z | z), bh(v.w | z)}, A1 = cmulc(A0, m), A2 = cmulc(A1, m), A3 = cmulc(A2, m);
                mma_f16(acc[0], hb(A0.r), hb(A1.r), hb(A0.i), hb(A1.i), u.x, u.y);
                mma_f16(acc[2], hb(A0.r), hb(A1.r), hb(A0.i), hb(A1.i), u.z, u.w);
                mma_f16(acc[4], hb(A0.r), hb(A1.r), hb(A0.i), hb(A1.i), v.x, v.y);
                mma_f16(acc[1], hb(A2.r), hb(A3.r), hb(A2.i), hb(A3.i), u.x, u.y);
                mma_f16(acc[3], hb(A2.r), hb(A3.r), hb(A2.i), hb(A3.i), u.z, u.w);
            }
        }
    }
    TS(40);
    uint32_t tag;
    asm volatile("add.u32 %0, %1, 1;" : "=r"(tag) : "r"(epoch));
    bar_sync(barid, s5cta ? 160 : 128);
    if (w == 3) {
        int it = 0;
        while (!__all_sync(0xffffffffu, ((fv.x ^ tag) | (fv.y ^ tag) | (fv.z ^ tag) | (fv.w ^ tag)) == 0)) {
            __nanosleep(100);
            fv = ld_flag4(fp);
            if (++it > POLL_LIMIT) __trap();
        }
        {
            fence_async_glob();
            mbar_expect(ubar, 4096 + 3072);
            bulk_ld(R + R_LIN, &g_scr.uT[ch * 256], 3072, ubar);
            tma2(R + R_U, &P.mu, 0, ch * 32, ubar);
        }
        TS(41);
    }
    {
#pragma unroll
        for (int i = 0; i < 10; i++) sts32(RP + w * 1280 + i * 128 + lane * 4, packh(acc[i >> 1][2 * (i & 1)], acc[i >> 1][2 * (i & 1) + 1]));
        sts32(R + R_K0 + w * 4 + (lane & 1) * 16, __float_as_uint((lane & 1) ? 2.f * dt * __uint_as_float(cm) : k0));
        if (tid < 104) sts128(R + (tid < 84 ? R_FAR : tid < 87 ? R_LIN - 87 * 16 : R_NEAR - 87 * 16) + tid * 16, 0, 0, 0, 0);
        if (tid < 65) sts128(R + R_U - 1040 + tid * 16, 0, 0, 0, 0);
    }
    fence_async_smem();
    bar_sync(barid, 128);
    {
        const uint4 k = lds128(R + R_K0), f = lds128(R + R_K0 + 16);
        uint32_t va[3], vb[3];
#pragma unroll
        for (int i = 0; i < 3; i++) {
            const uint32_t a = RP + (i < 2 ? 2 * w + i : 8 + (w & 1)) * 128 + lane * 4;
            const uint32_t p0 = lds32(a), p1 = lds32(a + 1280), p2 = lds32(a + 2560), p3 = lds32(a + 3840);
            const float2 q0 = __half22float2(*reinterpret_cast<const __half2*>(&p0)), q1 = __half22float2(*reinterpret_cast<const __half2*>(&p1)),
                         q2 = __half22float2(*reinterpret_cast<const __half2*>(&p2)), q3 = __half22float2(*reinterpret_cast<const __half2*>(&p3));
            float s0 = fmaf(q0.x, __uint_as_float(f.x), fmaf(q1.x, __uint_as_float(f.y), fmaf(q2.x, __uint_as_float(f.z), q3.x * __uint_as_float(f.w))));
            float s1 = fmaf(q0.y, __uint_as_float(f.x), fmaf(q1.y, __uint_as_float(f.y), fmaf(q2.y, __uint_as_float(f.z), q3.y * __uint_as_float(f.w))));
            if (i == 2 || (w >= 2 && t >= 2)) { s0 *= 0.5f; s1 *= 0.5f; }
            va[i] = packbf(s1, s0); vb[i] = packbf(s0, s1);
        }
        const uint32_t nb = R + R_NEAR + 256;
        const int i0 = g + 16 * (w & 1);
        if (w < 2) {
            const uint32_t a = nb + (8 * i0 + 1 + 2 * t) * 4;
#pragma unroll
            for (int h = 0; h < 2; h++) { sts16(a + h * 256, vb[h]); sts32(a + h * 256 + 4, va[h]); sts16(a + h * 256 + 10, va[h]); }
            const uint32_t a4 = R + R_FAR + (8 + FARW * (g & 1) + (g >> 1) + 4 * w + 16 * t) * 4;
            sts16(a4, vb[2]); sts16(a4 + 6, vb[2]); sts16(a4 + 32, va[2]); sts16(a4 + 38, va[2]);
            const float s0 = (__uint_as_float(k.x) + __uint_as_float(k.y)) + (__uint_as_float(k.z) + __uint_as_float(k.w));
            const uint32_t vs = tid == 63 ? va[1] : packbf(fmaf(2.f * dt, s0, dskip), 0.f), as = nb + (tid == 63 ? 257 * 4 : 0);
            sts16(as, vs); sts16(as + 6, vs);
        } else if (t < 2) {
            const uint32_t a = nb + (258 + 8 * i0 + 4 * t) * 4;
#pragma unroll
            for (int h = 0; h < 2; h++) {
                const uint32_t vv = __byte_perm(va[h], 0, 0x1010);
                const bool last = h == 1 && tid == 125;
                sts16(a + h * 256, vb[h]); sts32(a + h * 256 + 4, va[h]); sts64(a + h * 256 + 8, vv, last ? vv << 16 : vv);
                if (!last) sts16(a + h * 256 + 18, vv);
            }
        } else {
            const uint32_t a = R + R_FAR + (8 + 2 * FARW + i0 + 32 * (t - 2)) * 4;
#pragma unroll
            for (int h = 0; h < 2; h++) {
                sts16(a + h * 32, vb[h]); sts16(a + h * 32 + 6, vb[h]);
                sts16(a + h * 32 + FARW * 4, va[h]); sts16(a + h * 32 + FARW * 4 + 6, va[h]);
            }
        }
    }
    bar_sync(barid, 128);
    if (w == 2 && s5cta) mbar_arrive(SB + OFF_BAR + B_KG * 8);
    TS(42);
    const int lm = lane >> 3, lr = lane & 7;
    {
        const bool r3 = role >= 2;
        const uint32_t one = 0x3f803f80u | z;
        const int sh = g - 2 * t + 6;
#define BP0(l2, h2, l3, h3, c) (((r3 ? bandm(l3, h3, c) : bandm(l2, h2, c)) << sh) & 0x40004000u)
#define BP(l2, h2, l3, h3, c) mulbf2(BP0(l2, h2, l3, h3, c), one)
        const uint32_t bA[4] = {mulbf2(z, one), BP(6, 10, 12, 20, 3), BP(3, 5, 5, 11, 2), BP(6, 10, 12, 20, 2)};
        const uint32_t bB[4] = {BP(3, 5, 5, 11, 1), BP(6, 10, 12, 20, 1), BP(3, 5, 5, 11, 0), BP(6, 10, 12, 20, 0)};
        uint32_t kv = lds16(R + (r3 ? R_FAR + (8 + 3 * FARW + 63) * 4 : R_NEAR + 256 + 512 * 4));
        kv = packbf(bflo(kv) * (r3 ? 1.f : 0.5f), bflo(kv) * (r3 ? 1.f : 0.5f));
        const uint32_t e1 = mulbf2(BP0(1, 2, 3, 4, 1), kv), e0 = mulbf2(BP0(1, 2, 3, 4, 0), kv);
        uint32_t T[2][5][4];
#pragma unroll
        for (int q = 0; q < 2; q++) {
            const uint32_t ta = R + R_FAR + ((r3 ? 0 : 2 * FARW) + q * FARW + 2 + sh) * 4;
#pragma unroll
            for (int d = 0; d < 5; d++) {
                T[q][d][0] = lds32(ta + d * 64);
                T[q][d][1] = d < 4 ? lds32(ta + d * 64 + 32) : mulbf2(T[q][d][0], z);
                T[q][d][2] = d ? mulbf2(T[q][d - 1][1], one) : mulbf2(T[q][d][0], z);
                T[q][d][3] = mulbf2(T[q][d][0], one);
            }
        }
        const int cs = r3 ? 2 : 1;
        int rho = (r3 ? role - 2 : 64 * role) + (8 * (lm & 1) + lr) * cs;
        uint32_t la = R + R_LIN + ((r3 ? role - 2 : 64 * role) + lr * cs + lm - 3) * 16;
        float c[4][4];
#pragma unroll
        for (int d = 0; d < 4; d++) { c[d][0] = c[d][1] = c[d][2] = c[d][3] = 0.f; }
        const float zc[4] = {0.f, 0.f, 0.f, 0.f};
        bar_sync(barid, 128);
        mbar_wait(ubar, uphase);
        TS(43);
        const uint32_t st = 256u << (role >> 1);
        uint32_t lb = la + (st >> 1);
        uint4 x0 = ldsm4(la), x1 = ldsm4(lb);
        uint32_t m = r3 ? 0xfu : role ? 0xf0u : 0xffu;
        rho = (rho << 4) + (role >> 1) * (R_F3 - R_F2);
#pragma unroll 1
        do {
            float d0[4], d1[4], o[4];
            mma_bf16_c(d0, bA, x0.x, x0.y, zc); mma_bf16_c(d1, bA, x1.x, x1.y, zc);
            const uint32_t xa[4] = {x0.z | z, x1.z | z, x0.w | z, x1.w | z};
            mma_bf16(c[0], make_uint4(xa[0], xa[1], xa[2], xa[3]), e1, e0);
            mma_bf16_c(d0, bB, x0.z, x0.w, d0); mma_bf16_c(d1, bB, x1.z, x1.w, d1);
            la += st; lb += st;
            x0 = ldsm4(la); x1 = ldsm4(lb);
            far_apply(o, c, T, packbf(d0[0], d0[1]), packbf(d1[0], d1[1]), packbf(d0[2], d0[3]), packbf(d1[2], d1[3]), m);
            asm volatile("{\n.reg .pred p;\n.reg .b32 r;\nand.b32 r, %3, 1;\nsetp.ne.u32 p, r, 0;\n"
                         "@p stmatrix.sync.aligned.m8n8.x2.shared.b16 [%0], {%1,%2};\n}"
                         ::"r"(R + R_F2 + (rho ^ ((rho >> 3) & 0x70))), "r"(packbf(o[0], o[1])), "r"(packbf(o[2], o[3])), "r"(m) : "memory");
            rho += st; m >>= 1;
        } while (m);
    }
    if (s5cta && role >= 2) {
        const int v = cload + role;
        const uint32_t fb = SB + OFF_BAR + (B_FULL2 + v) * 8;
        mbar_wait(SB + OFF_BAR + B_G1 * 8, 0);
        mbar_expect(fb, 16384);
        tma5(SB + (v + 1) * SLOT, &P.mc, (v == 0 ? pj : v - 1 + (v - 1 >= pj)) * 64, pj * 4, 0, fb);
    }
    __syncwarp();
    TS(44);
    float y[16];
#pragma unroll
    for (int i = 0; i < 16; i++) y[i] = 0.f;
    {
        uint32_t fa[9][4];
        uint32_t ta = R + R_NEAR + (64 + 16 * w - 56 + g - 2 * t) * 4;
        uint64_t du = mkdesc(R + R_U + 96, 16, 1024, 1);
#pragma unroll 1
        for (int b = 0; b < 4; b++) {
            load_toep<9>(fa, ta, z);
            WG_FENCE();
#pragma unroll
            for (int i = 0; i < 9; i++) wgmma_rs32(y, fa[i], du - 2 * i);
            WG_COMMIT();
            WG_WAIT(0);
            ta += 18 * 32; du -= 18;
        }
        pin(y);
    }
    bar_sync(barid, 128);
    TS(45);
    {
        const uint32_t a = R + (8 * (lm >> 1) + lr) * 128 + (((2 * w + (lm & 1)) ^ lr) << 4);
        const uint2 f1 = ldsm2t(a + R_F2);
        const uint4 f2 = ldsm4t(a + R_F2 + 1024), f3 = ldsm4t(a + R_F3);
        y[4] += bflo(f1.x); y[5] += bfhi(f1.x); y[6] += bflo(f1.y); y[7] += bfhi(f1.y);
        y[8] += bflo(f2.x) + bflo(f3.x); y[9] += bfhi(f2.x) + bfhi(f3.x); y[10] += bflo(f2.y) + bflo(f3.y); y[11] += bfhi(f2.y) + bfhi(f3.y);
        y[12] += bflo(f2.z) + bflo(f3.z); y[13] += bfhi(f2.z) + bfhi(f3.z); y[14] += bflo(f2.w) + bflo(f3.w); y[15] += bfhi(f2.w) + bfhi(f3.w);
        stsm4t(a + R_U, packbf(y[0], y[1]), packbf(y[2], y[3]), packbf(y[4], y[5]), packbf(y[6], y[7]));
        stsm4t(a + R_U + 2048, packbf(y[8], y[9]), packbf(y[10], y[11]), packbf(y[12], y[13]), packbf(y[14], y[15]));
    }
    fence_async_smem();
    bar_sync(barid, 128);
    if (w == 0) {
        bulk_st(&g_scr.aT[ch * 256], R + R_U, 4096);
        bulk_wait();
        st_flag(&g_scr.flagA[ch], tag);
    }
    TS(46);
}

__device__ __forceinline__ float2 cexp2(float ar2, float ai, float k) {
    float m = ex2(ar2 * k), a = ai * k;
    return make_float2(m * fcos(a), m * fsin(a));
}
__device__ __forceinline__ float2 cfma(float2 a, float2 b, float2 c) {
    return make_float2(fmaf(a.x, b.x, fmaf(-a.y, b.y, c.x)), fmaf(a.x, b.y, fmaf(a.y, b.x, c.y)));
}

__global__ void __launch_bounds__(NTHREADS, 1) fused_kernel(const __grid_constant__ Params P) {
    extern __shared__ __align__(1024) char smem[];
    constexpr uint32_t sb = SB;
    constexpr uint32_t bar = sb + OFF_BAR;
    const int warp = __shfl_sync(0xffffffffu, threadIdx.x >> 5, 0), lane = threadIdx.x & 31, wg = warp >> 2, w = warp & 3;
    const int cta = (int)blockIdx.x - P.nextra;
    const int chunk = cta / 7, pj = cta - chunk * 7;
    uint32_t* const ep = &g_scr.epoch[blockIdx.x * 24 + warp];
    TS(warp == 0 ? 0 : 63);
    if (warp == 19) TSG(61);

    if (warp == 0 && cta >= 0) {
        {
            const uint32_t c = 0x100000u - (lane < B_G1 ? 1 : lane == B_FULL2 || lane == B_KG ? 3 : 2);
            if (lane < B_U || lane >= B_CNT) sts64(bar + lane * 8, lane < B_U ? c << 1 : 0, lane < B_U ? c << 11 : 0);
            fence_async_smem();
            __syncwarp();
        }
        TS(2);
#pragma unroll 1
        for (int s = 0; s < 3; s++) {
            const uint32_t fb = bar + (B_FULL1 + s) * 8;
            mbar_expect(fb, 32768);
            tma4(sb + (2 * s + 1) * SLOT, &P.mb, s * 64, pj * 8, fb);
            tma5(sb + (s == pj ? 7 : 2 * s + 2) * SLOT, &P.mx, s * 64, 0, chunk, fb);
        }
        if (lane >= 3 && lane < 8)
            asm volatile("mbarrier.arrive.expect_tx.shared::cta.b64 _, [%0], %1;" ::"r"(bar + lane * 8),
                         "r"(lane == B_XO ? (pj >= 3 ? 16384 + 128 : 128) : lane == pj ? 16384 : 32768) : "memory");
        __syncwarp();
        if (pj >= 3) tma5(sb + OFF_XOWN, &P.mx, pj * 64, 0, chunk, bar + B_XO * 8);
        bulk_ld(sb + OFF_GW, P.gw + pj * 64, 128, bar + B_XO * 8);
        if (chunk >= 3 && chunk < 7)
            asm volatile(EL "cp.async.bulk.prefetch.tensor.4d.L2.global.tile [%0, {%1, %3, %3, %2}];\n}" ::"l"(&P.mb), "r"(chunk * 64), "r"(pj * 8), "r"(0) : "memory");
        if ((uint32_t)__cvta_generic_to_shared(smem) != sb) __trap();
        TS(1);
    }
    if (warp == 1 && lane < 4) asm volatile("prefetch.tensormap [%0];" ::"l"(&P.mc + lane) : "memory");
    if (cta >= 0 && wg < 2) {
        if (warp == 0) {
#pragma unroll
            for (int i = 3; i < 6; i++) asm volatile("bar.arrive %0, 160;" ::"r"(i) : "memory");
        }
        const int hw = wg, g = lane >> 2, t = lane & 3, lm = lane >> 3, lr = lane & 7;
        const int pl = warp * 8 + g, p = pj * 64 + pl;
        const uint32_t epoch = ld_flag(ep);
        const float Lre = bf1(P.Lre + p), Lim = bf1(P.Lim + p), ldt = bf1(P.logdtB + p);
        const uint32_t db2 = ldg32(P.DB + pj * 64 + 16 * w + 2 * g);
        uint2* const myagg = &g_scr.agg[cta * 64 + pl];
        if (t == 3) *myagg = make_uint2(0u, 0u);
        if (warp == 2) g_scr.flag[cta * 32 + lane] = 0;
        if (warp == 3 && chunk == 0) *reinterpret_cast<uint2*>(&g_scr.flagA[pj * 64 + 2 * lane]) = make_uint2(0u, 0u);
        bar_sync(0, 256);
        constexpr uint32_t xo = sb + OFF_XOWN;
        const float dt = bfround(ex2(ldt * LOG2E));
        float ar2 = Lre * dt * LOG2E, ai = P.swapB ? -Lim * dt : Lim * dt;
        const float2 lam = cexp2(ar2, ai, 1.f), l16 = cexp2(ar2, ai, 16.f);
        const float2 zero2 = make_float2(0.f, 0.f);
        const float2 l32 = cfma(l16, l16, zero2), l64 = cfma(l32, l32, zero2);
        const float li = P.swapB ? -lam.y : lam.y;
        float m00, m01, m10, m11;
        {
            const float inv = 2.f * frcp(Lre * Lre + Lim * Lim), nr = lam.x - 1.f;
            const float sr = (nr * Lre + li * Lim) * inv, si = (li * Lre - nr * Lim) * inv;
            m00 = P.swapB ? -si : sr; m01 = P.swapB ? sr : -si; m10 = P.swapB ? -sr : -si; m11 = P.swapB ? -si : -sr;
        }
#define TSTAGE 0
        float acc[64], gd[4];
        uint32_t xt = XSLOT | (7u << (4 * pj)), bt = XSLOT;
#pragma unroll 1
        for (int s = 0; s < 7; s++, xt >>= 4, bt >>= 4) {
            const uint64_t da = desc(0x10040 - 1024 + hw * 512, HI128) + (bt & 15) * 1024, dx = desc(0x10040 | P.zero, HI128) + (xt & 15) * 1024;
            mbar_wait(bar + (B_FULL1 + s) * 8, 0);
            if (hw == 1) TS(30 + s);
            WG_FENCE();
#pragma unroll
            for (int k = 0; k < 4; k++) wgmma_n128(acc, da + 2 * k, dx + 2 * k, s | k);
            WG_COMMIT();
            WG_WAIT(1);
            if (w == 1) {
                if (s >= 1 && s < 5 && second_arrival(bar + B_CNT * 8 + s * 4)) {
                    const uint32_t dst = sb + ((bt >> 8) & 15) * SLOT, fb = bar + (B_FULL1 + s + 2) * 8;
                    if (s + 2 != pj) tma5(dst, &P.mx, s * 64 + 128, 0, chunk, fb);
                    tma4(dst - SLOT, &P.mb, s * 64 + 128, pj * 8, fb);
                }
                __syncwarp();
            }
            if (s == TSTAGE + 2) {
                if (w == 2) asm volatile(EL "cp.async.bulk.prefetch.L2.global [%0], %1;\n}" ::"l"((hw ? P.Cr : P.Ci) + cta * 3584), "r"(3584) : "memory");
                bulk_wait();
                st_flag(&g_scr.flag[cta * 32 + warp], epoch + 1);
                TS(4 + hw);
            }
            if (s == TSTAGE) {
                mbar_wait(bar + B_XO * 8, 0);
                if (TSTAGE < 2) mbar_wait(bar + (B_FULL1 + 2) * 8, 0);
                const uint32_t row = 2 * g + (t >> 1), sa = sb + warp * 2048 + row * 128 + (((4 * (t & 1)) ^ (row & 7)) << 4);
#pragma unroll
                for (int h = 0; h < 4; h++) {
                    const uint4 v = ldsm4t(xo + (8 * (4 * h + lm) + lr) * 128 + ((warp ^ lr) << 4));
                    sts128(sa ^ (h << 4), v.x, v.y, v.z, v.w);
                }
                fence_async_smem();
                __syncwarp();
                asm volatile(EL "cp.async.bulk.tensor.3d.global.shared::cta.bulk_group [%0, {%4, %2, %3}], [%1];\n}\ncp.async.bulk.commit_group;"
                             ::"l"(&P.ms), "r"(sb + warp * 2048), "r"(2 * chunk), "r"(pj * 64 + warp * 8), "r"(0) : "memory");
                if (warp == 4) TS(58);
            }
        }
        const uint32_t tag = epoch + 1, tag4 = epoch % 15u + 1u;
        st_flag(ep, tag);
        WG_WAIT(0);
        pin(acc);
        if (w == 0) mbar_arrive(bar + B_G1 * 8);
        TS(12 + hw);
#define AX(i) acc[4 * ((i) >> 1) + ((i) & 1)]
#define AY(i) acc[4 * ((i) >> 1) + 2 + ((i) & 1)]
        float2 e = make_float2(AX(0), AY(0)), e2 = make_float2(AX(16), AY(16));
#pragma unroll
        for (int i = 1; i < 16; i++) { e = cfma(lam, e, make_float2(AX(i), AY(i))); e2 = cfma(lam, e2, make_float2(AX(16 + i), AY(16 + i))); }
        e = cfma(l16, e, e2);
        {
            float2 o = make_float2(__shfl_up_sync(0xffffffffu, e.x, 1, 4), __shfl_up_sync(0xffffffffu, e.y, 1, 4));
            if (t >= 1) e = cfma(l32, o, e);
            o = make_float2(__shfl_up_sync(0xffffffffu, e.x, 2, 4), __shfl_up_sync(0xffffffffu, e.y, 2, 4));
            if (t >= 2) e = cfma(l64, o, e);
        }
        if (t == 3)
            asm volatile("st.relaxed.gpu.global.v2.u32 [%0], {%1,%2};" ::"l"(myagg), "r"((__float_as_uint(e.x) & ~15u) | tag4), "r"(__float_as_uint(e.y)) : "memory");
        WG_FENCE();
#pragma unroll
        for (int k = 0; k < 4; k++) wgmma_n8(gd, mkdesc(xo + hw * 8192, 16, 1024, 1) + 2 * k, mkdesc(sb + OFF_GW, 16, 128, 0) + 2 * k, k);
        WG_COMMIT();
        TS(14 + hw);
        float2 pre = make_float2(__shfl_up_sync(0xffffffffu, e.x, 1, 4), __shfl_up_sync(0xffffffffu, e.y, 1, 4));
        if (t == 0) pre = zero2;
        {
            const uint32_t zz = __float_as_uint(pre.x) & P.zero;
            m01 = __uint_as_float(__float_as_uint(m01) | zz); m11 = __uint_as_float(__float_as_uint(m11) | zz);
            ar2 = __uint_as_float(__float_as_uint(ar2) | zz); ai = __uint_as_float(__float_as_uint(ai) | zz);
        }
#pragma unroll
        for (int i = 0; i < 32; i++) {
            const float x = AX(i), y = AY(i);
            AX(i) = fmaf(m00, x, m01 * y); AY(i) = fmaf(m10, x, m11 * y);
        }
        WG_WAIT(0);
        pin(gd);
        if (t == 0) {
            uint32_t* gp = &g_scr.gpart[cta * 128 + 32 * (g >> 1) + 4 * warp + (g & 1)];
            st_flag(gp, (__float_as_uint(gd[0]) & ~15u) | tag4);
            st_flag(gp + 2, (__float_as_uint(gd[2]) & ~15u) | tag4);
        }
        {
            const float2 l512 = cexp2(ar2, ai, 512.f), l128t = cexp2(ar2, ai, 128.f * t), l32t = cexp2(ar2, ai, 32.f * t);
            uint2 v[4];
#pragma unroll
            for (int i = 0; i < 4; i++) v[i] = make_uint2(tag4, 0u);
            const uint2* src = myagg - (t + 1) * 448;
            int it = 0;
            while (true) {
                asm volatile("{\n.reg .pred p0, p1, p2, p3;\n"
                             "setp.gt.s32 p0, %9, 0;\nsetp.gt.s32 p1, %9, 4;\nsetp.gt.s32 p2, %9, 8;\nsetp.gt.s32 p3, %9, 12;\n"
                             "@p0 ld.relaxed.gpu.global.v2.u32 {%0,%1}, [%8];\n"
                             "@p1 ld.relaxed.gpu.global.v2.u32 {%2,%3}, [%8+-14336];\n"
                             "@p2 ld.relaxed.gpu.global.v2.u32 {%4,%5}, [%8+-28672];\n"
                             "@p3 ld.relaxed.gpu.global.v2.u32 {%6,%7}, [%8+-43008];\n}"
                             : "+r"(v[0].x), "+r"(v[0].y), "+r"(v[1].x), "+r"(v[1].y), "+r"(v[2].x), "+r"(v[2].y), "+r"(v[3].x), "+r"(v[3].y)
                             : "l"(src), "r"(chunk - t) : "memory");
                const uint32_t bad = (v[0].x ^ tag4) | (v[1].x ^ tag4) | (v[2].x ^ tag4) | (v[3].x ^ tag4);
                if (__all_sync(0xffffffffu, (bad & 15u) == 0)) break;
                if (++it > POLL_LIMIT) __trap();
            }
            float2 c = make_float2(__uint_as_float(v[3].x), __uint_as_float(v[3].y));
#pragma unroll
            for (int i = 2; i >= 0; i--) c = cfma(l512, c, make_float2(__uint_as_float(v[i].x), __uint_as_float(v[i].y)));
            c = cfma(l128t, c, zero2);
            c.x += __shfl_xor_sync(0xffffffffu, c.x, 1); c.y += __shfl_xor_sync(0xffffffffu, c.y, 1);
            c.x += __shfl_xor_sync(0xffffffffu, c.x, 2); c.y += __shfl_xor_sync(0xffffffffu, c.y, 2);
            pre = cfma(l32t, c, pre);
        }
        TS(16 + hw);
        mbar_wait(bar + B_KG * 8, 0);
        {
            const float2 lc = make_float2(lam.x, -li);
            float2 h = make_float2(fmaf(m00, pre.x, m01 * pre.y), fmaf(m10, pre.x, m11 * pre.y));
            const uint32_t hb = sb + 11 * SLOT + warp * 4096;
            const uint32_t ha = hb + (lm >> 1) * 2048 + (lm & 1) * 128 + lr * 16;
#pragma unroll
            for (int j = 0; j < 8; j++) {
                float2 h0 = cfma(lc, h, make_float2(AX(4 * j), AY(4 * j)));
                float2 h1 = cfma(lc, h0, make_float2(AX(4 * j + 1), AY(4 * j + 1)));
                float2 h2 = cfma(lc, h1, make_float2(AX(4 * j + 2), AY(4 * j + 2)));
                h = cfma(lc, h2, make_float2(AX(4 * j + 3), AY(4 * j + 3)));
                stsm4(ha + j * 256, packbf(h0.x, h1.x), packbf(h2.x, h.x), packbf(h0.y, h1.y), packbf(h2.y, h.y));
            }
            fence_async_smem();
            __syncwarp();
            TS(18 + hw);
            bulk_st(&g_scr.h[(cta * 8 + warp) * 256], hb, 4096);
        }
        float o[32];
        {
            const uint32_t xa = xo + (64 * hw + 2 * t) * 128 + (g & 3) * 4;
            const int q = 2 * w + (g >> 2);
#pragma unroll
            for (int j = 0; j < 8; j++)
#pragma unroll
                for (int k = 0; k < 2; k++) {
                    uint32_t v = lds32(xa + (8 * j + k) * 128 + ((q ^ (2 * t + k)) << 4));
                    asm("mul.rn.bf16x2 %0, %0, %1;" : "+r"(v) : "r"(db2));
                    o[4 * j + k] = bflo(v); o[4 * j + 2 + k] = bfhi(v);
                }
        }
        bar_sync(8 + hw, 128);
        if (w == 0) mbar_arrive(bar + B_FULL2 * 8);
        bulk_wait();
        st_flag(&g_scr.flag[cta * 32 + 8 + hw * 8 + w], tag);
        TS(20 + hw);
        {
            const uint32_t cre = P.swapC ? 512 : 0, cim = P.swapC ? 0 : 512;
            const uint32_t* fp = &g_scr.flag[(chunk * 7 + (lane < 14 ? lane >> 1 : 0)) * 32 + 8 + (lane & 1) * 8];
            const uint4* hsrc = &g_scr.h[chunk * 14336];
            const uint64_t dre = desc(0x10040 + cre, HI128), dim = desc(0x10040 + cim, HI128), dh0 = desc(0x1000040 + hw * 64, 8);
#define TILE2(co, ho) { WG_FENCE(); const uint64_t a_ = dre + (co), b_ = dim + (co), h_ = dh0 + (ho); \
            _Pragma("unroll") for (int k = 0; k < 8; k++) \
                wgmma_n64_tb(o, ((k & 2) ? b_ : a_) + ((k >> 2) * 4 + (k & 1) * 2), h_ + ((k >> 2) * 1024 + (k & 1) * 512 + (k & 2) * 64)); \
            WG_COMMIT(); }
            mbar_wait(bar + B_FULL2 * 8, 0);
            if (hw == 1) TS(47);
            TILE2(1024, 11 * 1024);
            WG_WAIT(0);
            if (w == 1) {
                mbar_arrive(bar + B_OWN * 8);
                if (hw == 0) {
                    int it = 0;
                    while (true) {
                        const uint4 f = ld_flag4(fp);
                        if (__all_sync(0xffffffffu, ((f.x ^ tag) | (f.y ^ tag) | (f.z ^ tag) | (f.w ^ tag)) == 0)) break;
                        if (++it > POLL_LIMIT) __trap();
                    }
                    TS(3);
                    fence_async_glob();
                    mbar_wait(bar + B_OWN * 8, 0);
#pragma unroll 1
                    for (int n = 1; n < 4; n++) {
                        mbar_expect(bar + (B_FULL2 + n) * 8, 32768);
                        bulk_ld(sb + ((HSLOT >> (4 * n)) & 15) * SLOT, hsrc + (n - 1 + (n - 1 >= pj)) * 2048, 32768, bar + (B_FULL2 + n) * 8);
                    }
                }
            }
            uint32_t hs = HSLOT >> 4, cs = CSLOT >> 4;
#pragma unroll 1
            for (int v = 1; v < 7; v++, hs >>= 4, cs >>= 4) {
                mbar_wait(bar + (B_FULL2 + v) * 8, 0);
                if (hw == 1) TS(47 + v);
                TILE2((cs & 15) * 1024, (hs & 15) * 1024);
                WG_WAIT(1);
                if (w == 1 && v >= 2 && v < 5 && second_arrival(bar + B_CNT * 8 + 12 + v * 4)) {
                    const uint32_t fb = bar + (B_FULL2 + v + 2) * 8;
                    mbar_expect(fb, 32768);
                    bulk_ld(sb + ((hs >> 8) & 15) * SLOT, hsrc + (v + 1 + (v + 1 >= pj)) * 2048, 32768, fb);
                    if (v == 2) {
                        mbar_expect(bar + (B_FULL2 + 6) * 8, 16384);
                        tma5(sb + 2 * SLOT, &P.mc, (pj == 6 ? 5 : 6) * 64, pj * 4, 0, bar + (B_FULL2 + 6) * 8);
                    }
                }
            }
        }
        TS(28 + hw);
        mbar_wait(bar + B_GA * 8, 0);
        {
            const int n7 = (2 * chunk + (t >> 1)) & 7, q = 4 * (t & 1) + 2 * hw;
            const uint32_t aa = sb + 9 * SLOT + (16 * w + 2 * g) * 256 + (t >> 1) * 128;
            uint4 a[4], gv[4];
#pragma unroll
            for (int i = 0; i < 2; i++) {
                a[i] = lds128(aa + (((q + i) ^ n7) << 4));
                a[2 + i] = lds128(aa + 256 + (((q + i) ^ n7) << 4));
            }
#pragma unroll
            for (int i = 0; i < 4; i++) gv[i] = lds128(sb + OFF_G + (32 * t + 16 * hw + 4 * i) * 4);
            WG_WAIT(0);
            pin(o);
            TS(24 + hw);
            float* op = P.out + (size_t)(chunk * 128 + 32 * t + 16 * hw) * D_ + pj * 64 + 16 * w + 2 * g;
            const uint32_t a0[8] = {a[0].x, a[0].y, a[0].z, a[0].w, a[1].x, a[1].y, a[1].z, a[1].w};
            const uint32_t a1[8] = {a[2].x, a[2].y, a[2].z, a[2].w, a[3].x, a[3].y, a[3].z, a[3].w};
            const uint32_t gg[16] = {gv[0].x, gv[0].y, gv[0].z, gv[0].w, gv[1].x, gv[1].y, gv[1].z, gv[1].w,
                                     gv[2].x, gv[2].y, gv[2].z, gv[2].w, gv[3].x, gv[3].y, gv[3].z, gv[3].w};
#pragma unroll
            for (int i = 0; i < 16; i++) {
                const float gt = __uint_as_float(gg[i]);
                const float b0 = o[4 * (i >> 1) + (i & 1)], b1 = o[4 * (i >> 1) + 2 + (i & 1)];
                const float x0 = (i & 1) ? bfhi(a0[i >> 1]) : bflo(a0[i >> 1]);
                const float x1 = (i & 1) ? bfhi(a1[i >> 1]) : bflo(a1[i >> 1]);
                *reinterpret_cast<float2*>(op + i * D_) = make_float2(fmaf(gt, x0 - b0, b0), fmaf(gt, x1 - b1, b1));
            }
            TS(26 + hw);
        }
    } else {
        constexpr int nx = D_ - NS5 * 3;
        int ch = cta < 0 ? (int)blockIdx.x + P.nextra * wg : nx + cta * 3 + (wg - 2);
        const int lim = cta < 0 ? (wg < P.nwg ? nx : 0) : D_, step = cta < 0 ? P.nextra * P.nwg : D_;
        const uint32_t R0 = sb + (wg + 2) * S4D_SZ, R = R0 + (wg == 3 ? 0 : SLOT);
        uint32_t phase = 0, epoch = 0;
        if (w == 3) { mbar_init(bar + (B_U + wg) * 8, 1); fence_async_smem(); }
#pragma unroll 1
        for (; ch < lim; ch += step) {
            int tid = threadIdx.x & 127;
            asm volatile("" : "+r"(tid));
            const int o = ch * 128 + tid;
            const uint32_t lar2 = ldg32(P.logA + o), aim2 = ldg32(P.Aim + o), cr2 = ldg32(P.Cre + o), ci2 = ldg32(P.Cim + o);
            const float logdt = bf1(P.logdtA + ch), dsk = bf1(P.DA + ch);
            epoch = ld_flag(ep + (tid & P.zero));
            TS(39);
            s4d_channel(P, ch, R0, R, 2 * wg - 6, pj, cta >= 0, bar + (B_U + wg) * 8, phase, 1 + wg, epoch, lar2, aim2, cr2, ci2, logdt, dsk, w, (w + wg) & 3, tid);
            phase ^= 1;
            if (cta < 0) bar_sync(1 + wg, 128);
        }
        const uint32_t tag = epoch + 1;
        st_flag(ep, tag);
        if (cta >= 0 && warp == 8) {
            const uint32_t tag4 = epoch % 15u + 1u;
            int it = 0;
            float z0, z1, z2, z3;
            while (true) {
                uint32_t bad = 0;
                z0 = z1 = z2 = z3 = 0.f;
#pragma unroll
                for (int i = 0; i < 7; i++) {
                    const uint4 v = ld_flag4(&g_scr.gpart[(chunk * 7 + i) * 128 + lane * 4]);
                    bad |= (v.x ^ tag4) | (v.y ^ tag4) | (v.z ^ tag4) | (v.w ^ tag4);
                    z0 += __uint_as_float(v.x); z1 += __uint_as_float(v.y); z2 += __uint_as_float(v.z); z3 += __uint_as_float(v.w);
                }
                if (__all_sync(0xffffffffu, (bad & 15u) == 0)) break;
                __nanosleep(200);
                if (++it > POLL_LIMIT) __trap();
            }
            sts128(sb + OFF_G + lane * 16, __float_as_uint(frcp(1.f + ex2(-LOG2E * z0))), __float_as_uint(frcp(1.f + ex2(-LOG2E * z1))),
                   __float_as_uint(frcp(1.f + ex2(-LOG2E * z2))), __float_as_uint(frcp(1.f + ex2(-LOG2E * z3))));
            TS(7);
            while (true) {
                const uint2 v = ld_flag2(&g_scr.flagA[pj * 64 + 2 * lane]);
                if (__all_sync(0xffffffffu, v.x == tag && v.y == tag)) break;
                __nanosleep(100);
                if (++it > POLL_LIMIT) __trap();
            }
            TS(8);
            {
                fence_async_glob();
                mbar_expect(bar + B_GA * 8, 16384);
                tma2(sb + 9 * SLOT, &P.ma, chunk * 128, pj * 64, bar + B_GA * 8);
            }
        }
    }
    TSDUMP();
}

typedef CUresult (*EncodeFn)(CUtensorMap*, CUtensorMapDataType, cuuint32_t, void*, const cuuint64_t*, const cuuint64_t*,
                             const cuuint32_t*, const cuuint32_t*, CUtensorMapInterleave, CUtensorMapSwizzle,
                             CUtensorMapL2promotion, CUtensorMapFloatOOBfill);

}

extern "C" void kernel_launch(void* const* d_in, const int* in_sizes, int n_in, void* d_out, int out_size) {
    (void)in_sizes; (void)n_in; (void)out_size;
    static EncodeFn enc = nullptr;
    static int nsm = 0;
    static char* scr = nullptr;
    if (!enc) {
        void* fn = nullptr;
        cudaDriverEntryPointQueryResult qr;
        cudaGetDriverEntryPoint("cuTensorMapEncodeTiled", &fn, cudaEnableDefault, &qr);
        enc = (EncodeFn)fn;
        cudaGetSymbolAddress((void**)&scr, g_scr);
        cudaDeviceGetAttribute(&nsm, cudaDevAttrMultiProcessorCount, 0);
        cudaFuncSetAttribute(fused_kernel, cudaFuncAttributeMaxDynamicSharedMemorySize, SMEM_BYTES);
    }
    Params P;
    const cuuint32_t es[5] = {1, 1, 1, 1, 1};
    const cuuint64_t RB = D_ * 2;
    {
        cuuint64_t gd[5] = {D_, 2, 4, 16, 16}, gs[4] = {RB, 32 * RB, 2 * RB, 128 * RB};
        cuuint32_t bx[5] = {64, 2, 4, 16, 1};
        enc(&P.mx, CU_TENSOR_MAP_DATA_TYPE_BFLOAT16, 5, d_in[0], gd, gs, bx, es, CU_TENSOR_MAP_INTERLEAVE_NONE,
            CU_TENSOR_MAP_SWIZZLE_128B, CU_TENSOR_MAP_L2_PROMOTION_L2_128B, CU_TENSOR_MAP_FLOAT_OOB_FILL_NONE);
    }
    {
        char *a = (char*)d_in[10], *b = (char*)d_in[11];
        P.swapB = b < a;
        cuuint64_t gd[4] = {D_, 8, 2, 56}, gs[3] = {RB, (cuuint64_t)(P.swapB ? a - b : b - a), 8 * RB};
        cuuint32_t bx[4] = {64, 8, 2, 8};
        enc(&P.mb, CU_TENSOR_MAP_DATA_TYPE_BFLOAT16, 4, P.swapB ? b : a, gd, gs, bx, es, CU_TENSOR_MAP_INTERLEAVE_NONE,
            CU_TENSOR_MAP_SWIZZLE_128B, CU_TENSOR_MAP_L2_PROMOTION_L2_128B, CU_TENSOR_MAP_FLOAT_OOB_FILL_NONE);
    }
    {
        char *a = (char*)d_in[12], *b = (char*)d_in[13];
        P.swapC = b < a;
        cuuint64_t gd[5] = {D_, 8, 2, 28, 2}, gs[4] = {2 * RB, RB, 16 * RB, (cuuint64_t)(P.swapC ? a - b : b - a)};
        cuuint32_t bx[5] = {64, 8, 2, 4, 2};
        enc(&P.mc, CU_TENSOR_MAP_DATA_TYPE_BFLOAT16, 5, P.swapC ? b : a, gd, gs, bx, es, CU_TENSOR_MAP_INTERLEAVE_NONE,
            CU_TENSOR_MAP_SWIZZLE_128B, CU_TENSOR_MAP_L2_PROMOTION_L2_128B, CU_TENSOR_MAP_FLOAT_OOB_FILL_NONE);
        P.Cr = a; P.Ci = b;
    }
    {
        cuuint64_t gd[2] = {L_, D_}, gs[1] = {L_ * 2};
        cuuint32_t bx[2] = {128, 64};
        enc(&P.ma, CU_TENSOR_MAP_DATA_TYPE_BFLOAT16, 2, scr + offsetof(Scratch, aT), gd, gs, bx, es, CU_TENSOR_MAP_INTERLEAVE_NONE,
            CU_TENSOR_MAP_SWIZZLE_NONE, CU_TENSOR_MAP_L2_PROMOTION_L2_128B, CU_TENSOR_MAP_FLOAT_OOB_FILL_NONE);
    }
    {
        cuuint64_t gd[2] = {64, D_ * 32}, gs[1] = {128};
        cuuint32_t bx[2] = {64, 32};
        enc(&P.mu, CU_TENSOR_MAP_DATA_TYPE_BFLOAT16, 2, scr + offsetof(Scratch, uT), gd, gs, bx, es, CU_TENSOR_MAP_INTERLEAVE_NONE,
            CU_TENSOR_MAP_SWIZZLE_128B, CU_TENSOR_MAP_L2_PROMOTION_L2_128B, CU_TENSOR_MAP_FLOAT_OOB_FILL_NONE);
    }
    {
        cuuint64_t gd[3] = {64, 32, D_}, gs[2] = {128, L_ * 2};
        cuuint32_t bx[3] = {64, 2, 8};
        enc(&P.ms, CU_TENSOR_MAP_DATA_TYPE_BFLOAT16, 3, scr + offsetof(Scratch, uT), gd, gs, bx, es, CU_TENSOR_MAP_INTERLEAVE_NONE,
            CU_TENSOR_MAP_SWIZZLE_128B, CU_TENSOR_MAP_L2_PROMOTION_NONE, CU_TENSOR_MAP_FLOAT_OOB_FILL_NONE);
    }
    P.zero = 0;
    P.logA = (const uint32_t*)d_in[1]; P.Aim = (const uint32_t*)d_in[2];
    P.Cre = (const uint32_t*)d_in[3]; P.Cim = (const uint32_t*)d_in[4];
    P.logdtA = (const uint16_t*)d_in[5]; P.DA = (const uint16_t*)d_in[6];
    P.Lre = (const uint16_t*)d_in[8]; P.Lim = (const uint16_t*)d_in[9];
    P.logdtB = (const uint16_t*)d_in[14]; P.DB = (const uint16_t*)d_in[15]; P.gw = (const uint16_t*)d_in[16];
    P.out = (float*)d_out;
    int nextra = nsm - NS5;
    if (nextra > 20) nextra = 20;
    if (nextra < 1) nextra = 1;
    P.nextra = nextra;
#define NWGX 4
    P.nwg = NWGX;
    fused_kernel<<<NS5 + nextra, NTHREADS, SMEM_BYTES, cudaStreamPerThread>>>(P);
}
```

```cpp
#include <cuda_runtime.h>
#include <cuda.h>
#include <cuda_bf16.h>
#include <cuda_fp16.h>
#include <stdint.h>
#include <stddef.h>

#define NB 3
#define SPL 2
#define SPLIT1 if (SPL & 1) BB_SPLIT(z)
#define SPLIT2 if (SPL & 2) BB_SPLIT(z)
#define SPLIT3 if (SPL & 4) BB_SPLIT(z)
#define TSTAGE 0
#define PACE 2
#define PACEN 4
#define PAUSE 1
#define FSTAGE 1
#define NH0 6
#define TB 0
#define XOS 1
#define LEAD 2
#define SDM 1
#define OPT 6
#define NCE 2
#define MAP 1
#define MAPOFF 4
#define SKEW 4
#define SKEW2 0
#define UE 7
#define US5 0
#define XE 0
#define FS 1
#define HH 1
#define DUAL 0
#define F1 0
#define ERF 0
#define RS 0
#define XPF 0
#define ROT 0x188
namespace {

constexpr int L_ = 2048, D_ = 448;
constexpr int NS5 = 112;
constexpr int NTHREADS = 640;
constexpr int MAXCTA = 132;

constexpr uint32_t SB = 1024;
constexpr int SLOT = 16384;
constexpr int OFF_XOWN = 7 * SLOT;
constexpr int S4D_SZ = 32768;
constexpr int OFF_BAR = 14 * SLOT;
constexpr int OFF_G = OFF_BAR + 256;
constexpr int OFF_GW = OFF_G + 1024;
constexpr int SMEM_BYTES = OFF_GW + 1024;
constexpr int B_FULL1 = 0, B_XO = 7, B_GA = 8, B_G1 = 9, B_FULL2 = 10, B_SD = 17, B_KG = 18, B_K2 = 19, B_U = 20, B_HF = 25, B_CNT = 26;
constexpr int R_F2 = 0, R_F3 = 3072, R_FAR = 3072, R_LIN = 5248, R_G = 4736, R_NB = 9584, R_U = 12288;
constexpr int FARW = 84;

struct __align__(128) Scratch {
    uint32_t epoch[MAXCTA * 24];
    uint32_t flag[NS5 * 32];
    uint32_t flagA[D_];
    uint2 agg[NS5 * 64];
    uint32_t gpart[NS5 * 128];
    uint4 uT[D_ * L_ / 8];
    uint4 aT[D_ * L_ / 8];
    uint4 h[NS5 * 2 * 1024];
};
__device__ Scratch g_scr;
#define TS(i)
#define TSDUMP()
#define TSG(i)

struct PatTab;
struct Params {
    int nextra, swapC;
    float sgnB;
    uint32_t zero, zs[4];
    Scratch* scr;
    const uint32_t *logA, *Aim, *Cre, *Cim;
    const uint16_t *logdtA, *DA, *Lre, *Lim, *logdtB, *DB, *gw;
    const PatTab* pat;
    const char *Cr, *Ci, *X;
    float* out;
    CUtensorMap mx, mb, mc, ma, mu, ms;
};

__device__ __forceinline__ float bflo(uint32_t v) { return __uint_as_float(v << 16); }
__device__ __forceinline__ float bfhi(uint32_t v) { return __uint_as_float(v & 0xffff0000u); }
__device__ __forceinline__ uint32_t ldg32(const void* p) {
    uint32_t v; asm volatile("ld.global.nc.u32 %0, [%1];" : "=r"(v) : "l"(p)); return v;
}
__device__ __forceinline__ uint32_t ldgv32(const void* p) {
    uint32_t v; asm volatile("ld.global.u32 %0, [%1];" : "=r"(v) : "l"(p) : "memory"); return v;
}
__device__ __forceinline__ uint32_t ldgv16(const void* p) {
    uint32_t v; asm volatile("ld.global.u16 %0, [%1];" : "=r"(v) : "l"(p) : "memory"); return v;
}
__device__ __forceinline__ float bf1(const uint16_t* p) {
    uint32_t v; asm volatile("ld.global.nc.u16 %0, [%1];" : "=r"(v) : "l"(p)); return __uint_as_float(v << 16);
}
__device__ __forceinline__ uint32_t packbf(float lo, float hi) {
    uint32_t r; asm("cvt.rn.bf16x2.f32 %0, %1, %2;" : "=r"(r) : "f"(hi), "f"(lo)); return r;
}
__device__ __forceinline__ uint32_t packh(float lo, float hi) {
    uint32_t r; asm("cvt.rn.f16x2.f32 %0, %1, %2;" : "=r"(r) : "f"(hi), "f"(lo)); return r;
}
__device__ __forceinline__ float bfround(float x) { return bflo(packbf(x, 0.f)); }
__device__ __forceinline__ float ex2(float x) { float r; asm("ex2.approx.ftz.f32 %0, %1;" : "=f"(r) : "f"(x)); return r; }
__device__ __forceinline__ float fsin(float x) { float r; asm("sin.approx.ftz.f32 %0, %1;" : "=f"(r) : "f"(x)); return r; }
__device__ __forceinline__ float fcos(float x) { float r; asm("cos.approx.ftz.f32 %0, %1;" : "=f"(r) : "f"(x)); return r; }
__device__ __forceinline__ float frcp(float x) { float r; asm("rcp.approx.ftz.f32 %0, %1;" : "=f"(r) : "f"(x)); return r; }
constexpr float LOG2E = 1.4426950408889634f;

struct C2 { __half2 r, i; };
__device__ __forceinline__ C2 cmul(C2 a, C2 b) {
    return C2{__hfma2(a.r, b.r, __hneg2(__hmul2(a.i, b.i))), __hfma2(a.r, b.i, __hmul2(a.i, b.r))};
}
__device__ __forceinline__ C2 cmulc(C2 a, C2 b) {
    return C2{__hfma2(a.r, b.r, __hmul2(a.i, b.i)), __hfma2(a.i, b.r, __hneg2(__hmul2(a.r, b.i)))};
}
__device__ __forceinline__ uint32_t hb(__half2 v) { return *reinterpret_cast<uint32_t*>(&v); }
__device__ __forceinline__ __half2 bh(uint32_t v) { return *reinterpret_cast<__half2*>(&v); }
__device__ __forceinline__ uint32_t mulbf2(uint32_t a, uint32_t b) {
    uint32_t r; asm volatile("mul.rn.bf16x2 %0, %1, %2;" : "=r"(r) : "r"(a), "r"(b)); return r;
}

#define EL "{\n.reg .pred q;\nelect.sync _|q, 0xffffffff;\n@q "
__device__ __forceinline__ void mbar_init(uint32_t bar, int cnt) {
    asm volatile(EL "mbarrier.init.shared::cta.b64 [%0], %1;\n}" ::"r"(bar), "r"(cnt) : "memory");
}
__device__ __forceinline__ void mbar_expect(uint32_t bar, uint32_t bytes) {
    asm volatile(EL "mbarrier.arrive.expect_tx.shared::cta.b64 _, [%0], %1;\n}" ::"r"(bar), "r"(bytes) : "memory");
}
__device__ __forceinline__ void mbar_arrive(uint32_t bar) {
    asm volatile(EL "mbarrier.arrive.shared::cta.b64 _, [%0];\n}" ::"r"(bar) : "memory");
}
__device__ __forceinline__ bool second_arrival(uint32_t a) {
    uint32_t v = 0;
    asm volatile(EL "atom.relaxed.cta.shared.exch.b32 %0, [%1], 1;\n}" : "+r"(v) : "r"(a) : "memory");
    return __any_sync(0xffffffffu, v != 0);
}
#define HINT ", 4000"
constexpr uint32_t WD_LIMIT = 1u << 19;
__device__ __forceinline__ void mbar_wait(uint32_t bar, uint32_t par, uint32_t& wd) {
    asm volatile(
        "{\n.reg .pred p, q;\n"
        "W%=:\nmbarrier.try_wait.parity.shared::cta.b64 p, [%1], %2" HINT ";\n"
        "add.u32 %0, %0, 1;\nsetp.lt.and.u32 q, %0, %3, !p;\n@q bra W%=;\n}" : "+r"(wd) : "r"(bar), "r"(par), "n"(WD_LIMIT) : "memory");
}
__device__ __forceinline__ bool all4(uint4 v, uint32_t tag) {
    return __all_sync(0xffffffffu, ((v.x ^ tag) | (v.y ^ tag) | (v.z ^ tag) | (v.w ^ tag)) == 0);
}
__device__ __forceinline__ void bar_sync(int id, int n) { asm volatile("bar.sync %0, %1;" ::"r"(id), "r"(n) : "memory"); }
__device__ __forceinline__ void fence_async_smem() { asm volatile("fence.proxy.async.shared::cta;" ::: "memory"); }
__device__ __forceinline__ void fence_async_glob() { asm volatile("fence.proxy.async.global;" ::: "memory"); }
__device__ __forceinline__ void tma2(uint32_t dst, const CUtensorMap* m, int c0, int c1, uint32_t bar) {
    asm volatile(EL "cp.async.bulk.tensor.2d.shared::cluster.global.mbarrier::complete_tx::bytes [%0], [%1, {%3, %4}], [%2];\n}"
                 ::"r"(dst), "l"(m), "r"(bar), "r"(c0), "r"(c1) : "memory");
}
__device__ __forceinline__ void tma4(uint32_t dst, const CUtensorMap* m, int c0, int c2, int c3, uint32_t bar) {
    asm volatile(EL "cp.async.bulk.tensor.4d.shared::cluster.global.mbarrier::complete_tx::bytes [%0], [%1, {%3, %6, %4, %5}], [%2];\n}"
                 ::"r"(dst), "l"(m), "r"(bar), "r"(c0), "r"(c2), "r"(c3), "r"(0) : "memory");
}
__device__ __forceinline__ void tma5(uint32_t dst, const CUtensorMap* m, int c0, int c3, int c4, uint32_t bar) {
    asm volatile(EL "cp.async.bulk.tensor.5d.shared::cluster.global.mbarrier::complete_tx::bytes [%0], [%1, {%3, %6, %6, %4, %5}], [%2];\n}"
                 ::"r"(dst), "l"(m), "r"(bar), "r"(c0), "r"(c3), "r"(c4), "r"(0) : "memory");
}
__device__ __forceinline__ void bulk_ld(uint32_t dst, const void* src, uint32_t n, uint32_t bar) {
    asm volatile(EL "cp.async.bulk.shared::cluster.global.mbarrier::complete_tx::bytes [%0], [%1], %2, [%3];\n}"
                 ::"r"(dst), "l"(src), "r"(n), "r"(bar) : "memory");
}
__device__ __forceinline__ void bulk_wait() { asm volatile("cp.async.bulk.wait_group 0;" ::: "memory"); __syncwarp(); }
__device__ __forceinline__ void bulk_st(void* dst, uint32_t src, uint32_t n) {
    asm volatile(EL "cp.async.bulk.global.shared::cta.bulk_group [%0], [%1], %2;\n}\ncp.async.bulk.commit_group;" ::"l"(dst), "r"(src), "r"(n) : "memory");
}
__device__ __forceinline__ void st_flag(uint32_t* p, uint32_t v) {
    asm volatile("st.relaxed.gpu.global.u32 [%0], %1;" ::"l"(p), "r"(v) : "memory");
}
__device__ __forceinline__ uint32_t ld_flag(const uint32_t* p) {
    uint32_t v; asm volatile("ld.relaxed.gpu.global.u32 %0, [%1];" : "=r"(v) : "l"(p) : "memory"); return v;
}
__device__ __forceinline__ uint2 ld_flag2(const void* p) {
    uint2 v; asm volatile("ld.relaxed.gpu.global.v2.u32 {%0,%1}, [%2];" : "=r"(v.x), "=r"(v.y) : "l"(p) : "memory"); return v;
}
__device__ __forceinline__ uint4 ld_flag4(const void* p) {
    uint4 v; asm volatile("ld.relaxed.gpu.global.v4.u32 {%0,%1,%2,%3}, [%4];" : "=r"(v.x), "=r"(v.y), "=r"(v.z), "=r"(v.w) : "l"(p) : "memory"); return v;
}
__device__ __forceinline__ uint32_t lds32(uint32_t a) { uint32_t v; asm volatile("ld.shared.u32 %0, [%1];" : "=r"(v) : "r"(a) : "memory"); return v; }
__device__ __forceinline__ uint32_t lds16(uint32_t a) { uint16_t v; asm volatile("ld.shared.u16 %0, [%1];" : "=h"(v) : "r"(a) : "memory"); return v; }
__device__ __forceinline__ uint4 lds128(uint32_t a) {
    uint4 v; asm volatile("ld.shared.v4.u32 {%0,%1,%2,%3}, [%4];" : "=r"(v.x), "=r"(v.y), "=r"(v.z), "=r"(v.w) : "r"(a) : "memory"); return v;
}
__device__ __forceinline__ void sts16(uint32_t a, uint32_t v) { asm volatile("st.shared.u16 [%0], %1;" ::"r"(a), "r"(v) : "memory"); }
#define sts16x2(a, off, v) asm volatile("st.shared.u16 [%0], %1;\nst.shared.u16 [%0+" #off "], %1;" ::"r"(a), "r"(v) : "memory")
__device__ __forceinline__ void sts32(uint32_t a, uint32_t v) { asm volatile("st.shared.u32 [%0], %1;" ::"r"(a), "r"(v) : "memory"); }
__device__ __forceinline__ void sts128(uint32_t a, uint32_t x, uint32_t y, uint32_t z, uint32_t w) {
    asm volatile("st.shared.v4.u32 [%0], {%1,%2,%3,%4};" ::"r"(a), "r"(x), "r"(y), "r"(z), "r"(w) : "memory");
}
__device__ __forceinline__ void sts64(uint32_t a, uint32_t x, uint32_t y) {
    asm volatile("st.shared.v2.u32 [%0], {%1,%2};" ::"r"(a), "r"(x), "r"(y) : "memory");
}
__device__ __forceinline__ uint2 ldsm2t(uint32_t a) {
    uint2 v; asm volatile("ldmatrix.sync.aligned.m8n8.x2.trans.shared.b16 {%0,%1}, [%2];" : "=r"(v.x), "=r"(v.y) : "r"(a) : "memory"); return v;
}
__device__ __forceinline__ uint2 ldsm2(uint32_t a) {
    uint2 v; asm volatile("ldmatrix.sync.aligned.m8n8.x2.shared.b16 {%0,%1}, [%2];" : "=r"(v.x), "=r"(v.y) : "r"(a) : "memory"); return v;
}
__device__ __forceinline__ void stsm2(uint32_t a, uint32_t x, uint32_t y) {
    asm volatile("stmatrix.sync.aligned.m8n8.x2.shared.b16 [%0], {%1,%2};" ::"r"(a), "r"(x), "r"(y) : "memory");
}
__device__ __forceinline__ void stsm2t(uint32_t a, uint32_t x, uint32_t y) {
    asm volatile("stmatrix.sync.aligned.m8n8.x2.trans.shared.b16 [%0], {%1,%2};" ::"r"(a), "r"(x), "r"(y) : "memory");
}
__device__ __forceinline__ bool mbar_test(uint32_t bar) {
    uint32_t p;
    asm volatile("{\n.reg .pred q;\nmbarrier.test_wait.parity.shared::cta.b64 q, [%1], 0;\nselp.u32 %0, 1, 0, q;\n}" : "=r"(p) : "r"(bar) : "memory");
    return p != 0;
}
__device__ __forceinline__ uint4 ldsm4(uint32_t a) {
    uint4 v; asm volatile("ldmatrix.sync.aligned.m8n8.x4.shared.b16 {%0,%1,%2,%3}, [%4];" : "=r"(v.x), "=r"(v.y), "=r"(v.z), "=r"(v.w) : "r"(a) : "memory"); return v;
}
__device__ __forceinline__ uint4 ldsm4t(uint32_t a) {
    uint4 v; asm volatile("ldmatrix.sync.aligned.m8n8.x4.trans.shared.b16 {%0,%1,%2,%3}, [%4];" : "=r"(v.x), "=r"(v.y), "=r"(v.z), "=r"(v.w) : "r"(a) : "memory"); return v;
}
__device__ __forceinline__ void stsm4(uint32_t a, uint32_t x, uint32_t y, uint32_t z, uint32_t w) {
    asm volatile("stmatrix.sync.aligned.m8n8.x4.shared.b16 [%0], {%1,%2,%3,%4};" ::"r"(a), "r"(x), "r"(y), "r"(z), "r"(w) : "memory");
}
__device__ __forceinline__ void stsm4t(uint32_t a, uint32_t x, uint32_t y, uint32_t z, uint32_t w) {
    asm volatile("stmatrix.sync.aligned.m8n8.x4.trans.shared.b16 [%0], {%1,%2,%3,%4};" ::"r"(a), "r"(x), "r"(y), "r"(z), "r"(w) : "memory");
}
__device__ __forceinline__ void mma_f16(uint32_t (&d)[2], uint32_t a0, uint32_t a1, uint32_t a2, uint32_t a3, uint32_t b0, uint32_t b1) {
    asm volatile("mma.sync.aligned.m16n8k16.row.col.f16.f16.f16.f16 {%0,%1},{%2,%3,%4,%5},{%6,%7},{%0,%1};"
                 : "+r"(d[0]), "+r"(d[1]) : "r"(a0), "r"(a1), "r"(a2), "r"(a3), "r"(b0), "r"(b1));
}
__device__ __forceinline__ void mma_bf16(float (&d)[4], uint4 a, uint32_t b0, uint32_t b1) {
    asm volatile("mma.sync.aligned.m16n8k16.row.col.f32.bf16.bf16.f32 {%0,%1,%2,%3},{%4,%5,%6,%7},{%8,%9},{%0,%1,%2,%3};"
                 : "+f"(d[0]), "+f"(d[1]), "+f"(d[2]), "+f"(d[3]) : "r"(a.x), "r"(a.y), "r"(a.z), "r"(a.w), "r"(b0), "r"(b1));
}
__device__ __forceinline__ void mma_bf16_c(float (&d)[4], const uint32_t (&a)[4], uint32_t b0, uint32_t b1, const float (&c)[4]) {
    asm volatile("mma.sync.aligned.m16n8k16.row.col.f32.bf16.bf16.f32 {%0,%1,%2,%3},{%4,%5,%6,%7},{%8,%9},{%10,%11,%12,%13};"
                 : "=f"(d[0]), "=f"(d[1]), "=f"(d[2]), "=f"(d[3])
                 : "r"(a[0]), "r"(a[1]), "r"(a[2]), "r"(a[3]), "r"(b0), "r"(b1), "f"(c[0]), "f"(c[1]), "f"(c[2]), "f"(c[3]));
}
__device__ __forceinline__ void far_apply(float (&o)[4], float (&c)[4][4], const uint32_t (&T)[2][5][4], uint32_t p0, uint32_t p1,
                                          uint32_t q0, uint32_t q1) {
    asm volatile("mma.sync.aligned.m16n8k16.row.col.f32.bf16.bf16.f32 {%0,%1,%2,%3},{%20,%21,%22,%23},{%60,%61},{%4,%5,%6,%7};\n"
                 "mma.sync.aligned.m16n8k16.row.col.f32.bf16.bf16.f32 {%4,%5,%6,%7},{%24,%25,%26,%27},{%60,%61},{%8,%9,%10,%11};\n"
                 "mma.sync.aligned.m16n8k16.row.col.f32.bf16.bf16.f32 {%8,%9,%10,%11},{%28,%29,%30,%31},{%60,%61},{%12,%13,%14,%15};\n"
                 "mma.sync.aligned.m16n8k16.row.col.f32.bf16.bf16.f32 {%12,%13,%14,%15},{%32,%33,%34,%35},{%60,%61},{%16,%17,%18,%19};\n"
                 "mma.sync.aligned.m16n8k16.row.col.f32.bf16.bf16.f32 {%16,%17,%18,%19},{%36,%37,%38,%39},{%60,%61},{%64,%64,%64,%64};\n"
                 "mma.sync.aligned.m16n8k16.row.col.f32.bf16.bf16.f32 {%0,%1,%2,%3},{%40,%41,%42,%43},{%62,%63},{%0,%1,%2,%3};\n"
                 "mma.sync.aligned.m16n8k16.row.col.f32.bf16.bf16.f32 {%4,%5,%6,%7},{%44,%45,%46,%47},{%62,%63},{%4,%5,%6,%7};\n"
                 "mma.sync.aligned.m16n8k16.row.col.f32.bf16.bf16.f32 {%8,%9,%10,%11},{%48,%49,%50,%51},{%62,%63},{%8,%9,%10,%11};\n"
                 "mma.sync.aligned.m16n8k16.row.col.f32.bf16.bf16.f32 {%12,%13,%14,%15},{%52,%53,%54,%55},{%62,%63},{%12,%13,%14,%15};\n"
                 "mma.sync.aligned.m16n8k16.row.col.f32.bf16.bf16.f32 {%16,%17,%18,%19},{%56,%57,%58,%59},{%62,%63},{%16,%17,%18,%19};\n"
                 : "=&f"(o[0]), "=&f"(o[1]), "=&f"(o[2]), "=&f"(o[3]),
                   "+f"(c[0][0]), "+f"(c[0][1]), "+f"(c[0][2]), "+f"(c[0][3]), "+f"(c[1][0]), "+f"(c[1][1]), "+f"(c[1][2]), "+f"(c[1][3]),
                   "+f"(c[2][0]), "+f"(c[2][1]), "+f"(c[2][2]), "+f"(c[2][3]), "+f"(c[3][0]), "+f"(c[3][1]), "+f"(c[3][2]), "+f"(c[3][3])
                 : "r"(T[0][0][0]), "r"(T[0][0][1]), "r"(T[0][0][2]), "r"(T[0][0][3]), "r"(T[0][1][0]), "r"(T[0][1][1]), "r"(T[0][1][2]), "r"(T[0][1][3]), "r"(T[0][2][0]), "r"(T[0][2][1]), "r"(T[0][2][2]), "r"(T[0][2][3]), "r"(T[0][3][0]), "r"(T[0][3][1]), "r"(T[0][3][2]), "r"(T[0][3][3]), "r"(T[0][4][0]), "r"(T[0][4][1]), "r"(T[0][4][2]), "r"(T[0][4][3]), "r"(T[1][0][0]), "r"(T[1][0][1]), "r"(T[1][0][2]), "r"(T[1][0][3]), "r"(T[1][1][0]), "r"(T[1][1][1]), "r"(T[1][1][2]), "r"(T[1][1][3]), "r"(T[1][2][0]), "r"(T[1][2][1]), "r"(T[1][2][2]), "r"(T[1][2][3]), "r"(T[1][3][0]), "r"(T[1][3][1]), "r"(T[1][3][2]), "r"(T[1][3][3]), "r"(T[1][4][0]), "r"(T[1][4][1]), "r"(T[1][4][2]), "r"(T[1][4][3]),
                   "r"(p0), "r"(p1), "r"(q0), "r"(q1), "f"(0.f));
}
__device__ __forceinline__ void mma_bf16_k8(float (&d)[4], uint32_t a0, uint32_t a1, uint32_t b0) {
    asm volatile("mma.sync.aligned.m16n8k8.row.col.f32.bf16.bf16.f32 {%0,%1,%2,%3},{%4,%5},{%6},{%0,%1,%2,%3};"
                 : "+f"(d[0]), "+f"(d[1]), "+f"(d[2]), "+f"(d[3]) : "r"(a0), "r"(a1), "r"(b0));
}
__device__ __forceinline__ uint32_t addbf2(uint32_t a, uint32_t b) {
    uint32_t r; asm("add.rn.bf16x2 %0, %1, %2;" : "=r"(r) : "r"(a), "r"(b)); return r;
}
__device__ __forceinline__ uint32_t mulbf2n(uint32_t a, uint32_t b) {
    uint32_t r; asm("mul.rn.bf16x2 %0, %1, %2;" : "=r"(r) : "r"(a), "r"(b)); return r;
}
__device__ __forceinline__ uint32_t fmabf2(uint32_t a, uint32_t b, uint32_t c) {
    uint32_t r; asm("fma.rn.bf16x2 %0, %1, %2, %3;" : "=r"(r) : "r"(a), "r"(b), "r"(c)); return r;
}
__device__ __forceinline__ uint4 ldg128(const void* p) {
    uint4 v; asm volatile("ld.global.v4.u32 {%0,%1,%2,%3}, [%4];" : "=r"(v.x), "=r"(v.y), "=r"(v.z), "=r"(v.w) : "l"(p) : "memory"); return v;
}
struct alignas(16) PatTab { uint32_t v[4][4][32][4]; };
constexpr uint32_t band(int lo, int hi, int j, uint32_t one) {
    return (j >= lo && j <= hi ? one : 0u) | (j - 1 >= lo && j - 1 <= hi ? one << 16 : 0u);
}
constexpr PatTab make_pat() {
    PatTab p = {};
    for (int role = 0; role < 4; role++)
        for (int l = 0; l < 32; l++) {
            const bool r3 = role >= 2;
            const int d = (l >> 2) - 2 * (l & 3), cs = r3 ? 2 : 1, c0 = r3 ? role - 2 : 16 * NH0 * role;
            const bool mrg = r3 ? (l & 3) >= 2 : (l & 3) == 3;
            for (int k = 0; k < 6; k++) {
                const int c = k < 2 ? (r3 ? 2 : 9) : k < 4 ? 1 : mrg ? (r3 ? 3 : 2) : 0;
                p.v[role][k >= 2][l][k >= 2 ? k - 2 : k] = (k & 1) ? band(r3 ? 12 : 6, r3 ? 20 : 10, d + 8 * c, 0x3f80) : band(r3 ? 5 : 3, r3 ? 11 : 5, d + 8 * c, 0x3f80);
            }
            p.v[role][0][l][2] = mrg ? 0x3210 : 0x7654;
            p.v[role][0][l][3] = R_FAR + ((r3 ? 0 : 2 * FARW) + 8 + d) * 4;
            p.v[role][2][l][0] = band(r3 ? 3 : 1, r3 ? 4 : 2, d + 8, 0xffff);
            p.v[role][2][l][1] = band(r3 ? 3 : 1, r3 ? 4 : 2, d, 0xffff);
            p.v[role][2][l][2] = R_LIN + (c0 + (l & 15) * cs + (l >> 4) - 1) * 16;
            p.v[role][2][l][3] = (r3 ? R_F3 : R_F2) + (c0 + (l & 15) * cs) * 16;
            const int w = role, g = l >> 2, t = l & 3, i0 = g + 16 * (w & 1), nb = R_NB, fb = R_FAR + 32;
            const bool far = w >= 2 && t >= 2;
            const int A = w < 2 ? nb + (8 * i0 + 1 + 2 * t) * 4 : far ? fb + (2 * FARW - 64 + i0 + 32 * t) * 4 : nb + (290 + 8 * i0 + 4 * t) * 4;
            const int B = A + (far ? FARW * 4 : 4), C = A + (far ? FARW * 4 + 6 : w < 2 ? 10 : 18);
            const bool sw = !far && g >= 4;
            p.v[w][3][l][0] = sw ? (A + 6) | A << 16 : A | (A + 6) << 16;
            p.v[w][3][l][1] = sw ? C | B << 16 : B | C << 16;
            const int k = 32 * w + l;
            const int z0 = k < 84 ? R_FAR + k * 16 : k < 87 ? R_LIN + (k - 87) * 16 : k < 96 ? nb - 128 + (k - 87) * 16 : R_U + (k - 128) * 16;
            const int z1 = k < 9 ? nb + 1024 + k * 16 : R_U - 528;
            p.v[w][3][l][2] = (fb + (FARW * (g & 1) + (g >> 1) + 4 * w + 16 * t) * 4) | z0 << 16;
            p.v[w][3][l][3] = (nb + (w == 1 && l == 31 ? 289 * 4 : w == 3 && l == 29 ? 545 * 4 : 0)) | z1 << 16;
        }
    return p;
}
__device__ const PatTab g_pat = make_pat();
__device__ __forceinline__ uint64_t mkdesc(uint32_t addr, uint32_t lbo, uint32_t sbo, uint32_t swz) {
    uint32_t lo = (addr >> 4) | ((lbo >> 4) << 16), hi = (sbo >> 4) | (swz << 30);
    return ((uint64_t)hi << 32) | lo;
}
__device__ __forceinline__ uint64_t desc(uint32_t lo, uint32_t hi) { return ((uint64_t)hi << 32) | lo; }
constexpr uint32_t HI128 = 0x40000040u;
#define BB_SPLIT(z) asm volatile("{\n.reg .pred p;\nsetp.eq.u32 p, %0, 0;\n@p bra S%=;\ntrap;\nS%=:\n}" ::"r"(z) : "memory")
#define WG_FENCE() asm volatile("wgmma.fence.sync.aligned;" ::: "memory")
#define WG_COMMIT() asm volatile("wgmma.commit_group.sync.aligned;" ::: "memory")
#define WG_WAIT(n) asm volatile("wgmma.wait_group.sync.aligned " #n ";" ::: "memory")

template <int N>
__device__ __forceinline__ void pin(float (&d)[N]) {
#pragma unroll
    for (int i = 0; i < N; i++) asm volatile("" : "+f"(d[i])::"memory");
}
#define F4(d, o) "+f"(d[(o)]), "+f"(d[(o) + 1]), "+f"(d[(o) + 2]), "+f"(d[(o) + 3])
#define F8(d, o) F4(d, o), F4(d, (o) + 4)
#define F16(d, o) F8(d, o), F8(d, (o) + 8)
#define F32(d, o) F16(d, o), F16(d, (o) + 16)

__device__ __forceinline__ void wgmma_n128(float (&d)[64], uint64_t da, uint64_t db, int sd) {
    asm volatile("{\n.reg .pred p;\nsetp.ne.b32 p, %66, 0;\n"
        "wgmma.mma_async.sync.aligned.m64n128k16.f32.bf16.bf16 {%0,%1,%2,%3,%4,%5,%6,%7,%8,%9,%10,%11,%12,%13,%14,%15,"
        "%16,%17,%18,%19,%20,%21,%22,%23,%24,%25,%26,%27,%28,%29,%30,%31,%32,%33,%34,%35,%36,%37,%38,%39,%40,%41,%42,%43,%44,%45,%46,%47,"
        "%48,%49,%50,%51,%52,%53,%54,%55,%56,%57,%58,%59,%60,%61,%62,%63}, %64, %65, p, 1, 1, 0, 0;\n}\n"
        : F32(d, 0), F32(d, 32) : "l"(da), "l"(db), "r"(sd));
}
__device__ __forceinline__ void wgmma_n8(float (&d)[4], uint64_t da, uint64_t db, int sd) {
    asm volatile("{\n.reg .pred p;\nsetp.ne.b32 p, %6, 0;\n"
        "wgmma.mma_async.sync.aligned.m64n8k16.f32.bf16.bf16 {%0,%1,%2,%3}, %4, %5, p, 1, 1, 0, 0;\n}\n"
        : F4(d, 0) : "l"(da), "l"(db), "r"(sd));
}
__device__ __forceinline__ void wgmma_n64_tb(float (&d)[32], uint64_t da, uint64_t db, int sd) {
    asm volatile("{\n.reg .pred p;\nsetp.ne.b32 p, %34, 0;\n"
        "wgmma.mma_async.sync.aligned.m64n64k16.f32.bf16.bf16 {%0,%1,%2,%3,%4,%5,%6,%7,%8,%9,%10,%11,%12,%13,%14,%15,"
        "%16,%17,%18,%19,%20,%21,%22,%23,%24,%25,%26,%27,%28,%29,%30,%31}, %32, %33, p, 1, 1, 0, 1;\n}\n"
        : F32(d, 0) : "l"(da), "l"(db), "r"(sd));
}
__device__ __forceinline__ void wgmma_rs64(float (&d)[32], const uint32_t (&a)[4], uint64_t db, int sd) {
    asm volatile("{\n.reg .pred p;\nsetp.ne.b32 p, %37, 0;\n"
        "wgmma.mma_async.sync.aligned.m64n64k16.f32.bf16.bf16 {%0,%1,%2,%3,%4,%5,%6,%7,%8,%9,%10,%11,%12,%13,%14,%15,"
        "%16,%17,%18,%19,%20,%21,%22,%23,%24,%25,%26,%27,%28,%29,%30,%31}, {%32,%33,%34,%35}, %36, p, 1, 1, 0;\n}\n"
        : F32(d, 0) : "r"(a[0]), "r"(a[1]), "r"(a[2]), "r"(a[3]), "l"(db), "r"(sd));
}

__device__ __forceinline__ uint32_t shfl_quad(uint32_t v, int b) {
    uint32_t r; asm volatile("shfl.sync.idx.b32 %0, %1, %2, 0x31f, 0xffffffff;" : "=r"(r) : "r"(v), "r"(b)); return r;
}
__device__ __forceinline__ int fresh_lane() { int l; asm volatile("mov.u32 %0, %%laneid;" : "=r"(l)); return l; }
__device__ __forceinline__ uint32_t s4d_kgen(const Params& P, int ch, uint32_t R0, uint32_t R, bool s5cta, uint32_t ubar,
                                             int barid, uint32_t epoch, uint32_t lar2, uint32_t aim2, uint32_t cr2,
                                             uint32_t ci2, float logdt, float dskip, int w, int tid, bool lead, uint32_t& wd) {
    const int lane = tid & 31, g = lane >> 2, t = lane & 3;
    const float dt = bfround(ex2(logdt * LOG2E));
    const uint4 pD = ldg128(P.pat->v[w][3][lane]);
    const uint32_t X = SB + OFF_GW + 224 + barid * 32;
    uint32_t cm = __vmaxu2(cr2 & 0x7fff7fffu, ci2 & 0x7fff7fffu);
    sts32(X + w * 4, __reduce_max_sync(0xffffffffu, max(cm, cm << 16)));
    bar_sync(barid, s5cta ? 160 : 128);
    TS(37);
    {
        const uint4 c4 = lds128(X);
        cm = max(max(c4.x, c4.y), max(c4.z, c4.w)) & 0x7f800000u;
    }
    const float sc = __uint_as_float(0x7f000000u - cm);
    sts32(X + 16 + w * 4, __reduce_add_sync(0xffffffffu, __float2int_rn((bflo(cr2) + bfhi(cr2)) * sc * 1048576.f)));
    const uint32_t RP = 2 * R0 + SLOT - R;
    const uint32_t stg = R0 + w * 8192, z = P.zero;
    C2 w64;
    {
        const float dl = dt * LOG2E;
        const float r0 = ex2(-bfround(ex2(bflo(lar2) * LOG2E)) * dl), r1 = ex2(-bfround(ex2(bfhi(lar2) * LOG2E)) * dl);
        const float z0 = bflo(aim2) * dt, z1 = bfhi(aim2) * dt;
        float x0 = r0 * fcos(z0), y0 = r0 * fsin(z0), x1 = r1 * fcos(z1), y1 = r1 * fsin(z1);
#define PK() C2{bh(packh(x0, x1)), bh(packh(y0, y1))}
#define SQ() { float t0 = y0 * y0, u0 = x0 + x0, t1 = y1 * y1, u1 = x1 + x1; \
               x0 = fmaf(x0, x0, -t0); y0 = u0 * y0; x1 = fmaf(x1, x1, -t1); y1 = u1 * y1; }
        const C2 G0 = C2{bh(packh(bflo(cr2) * sc, bfhi(cr2) * sc)), bh(packh(bflo(ci2) * -sc, bfhi(ci2) * -sc))};
        const uint32_t my = stg + lane * 256 + (((lane & 1) | ((lane >> 1) & 2) | ((lane & 2) << 1)) << 4);
#define ST(c, a, b) { const C2 a_ = (a), b_ = (b); sts128((my ^ (((c) & 7) * 16)) + ((c) >> 3) * 128, hb(a_.r), hb(a_.i), hb(b_.r), hb(b_.i)); }
        const C2 b1 = PK(); SQ();
        const C2 b2 = PK(); SQ();
        const C2 b4 = PK(); SQ();
        const C2 b8 = PK(); SQ();
        const C2 w16 = PK(); SQ();
        const C2 b3 = cmul(b1, b2), G1 = cmulc(G0, b8), G2 = cmulc(G0, w16), G3 = cmulc(G1, w16);
        ST(1, b1, G0); ST(3, b2, G1); ST(5, b3, G2); ST(7, b4, G3);
        SPLIT1;
        const C2 w32 = PK(); SQ();
        w64 = PK(); SQ();
        const C2 b6 = cmul(b2, b4);
        ST(9, cmul(b1, b4), cmulc(G0, w32)); ST(11, b6, cmulc(G1, w32)); ST(13, cmul(b3, b4), cmulc(G2, w32)); ST(15, b8, cmulc(G3, w32));
        SPLIT2;
        const C2 w128 = PK(); SQ();
        const C2 w256 = PK(); SQ();
        const C2 w512 = PK();
        const C2 c5 = cmul(b8, w512), e0 = cmul(c5, w512);
        const C2 e1 = cmul(e0, w128), e2 = cmul(e0, w256), e3 = cmul(e1, w256);
        ST(0, cmul(b2, w256), e0); ST(2, cmul(b4, w256), e1); ST(4, cmul(b6, w256), e2); ST(6, cmul(b8, w256), e3);
        SPLIT3;
        const C2 c4 = cmul(b4, w512);
        ST(8, c4, cmul(e0, w512)); ST(10, c5, cmul(e1, w512));
        ST(12, cmul(c4, w256), cmul(e2, w512)); ST(14, cmul(c5, w256), cmul(e3, w512));
    }
    __syncwarp();
    if (LEAD == 1 && lead) asm volatile("bar.arrive 14, 512;" ::: "memory");
    TS(38);
    const uint32_t* fp = &P.scr->flag[((lane >> 1) * 7 + (ch >> 6)) * 32 + (lane & 1) * 4];
    uint4 fv = make_uint4(0u, 0u, 0u, 0u);
    uint32_t acc[5][2];
#pragma unroll
    for (int i = 0; i < 5; i++) acc[i][0] = acc[i][1] = 0u;
    {
        const uint32_t a = stg + t * 256 + ((g * 32) ^ (((t & 1) | ((t & 2) << 1)) << 4));
#define KLOAD(u, v, m, ks) u = lds128((a ^ (((ks) & 1) * 32)) + (ks) * 1024); v = lds128((a ^ (((ks) & 1) * 32 + 16)) + (ks) * 1024); \
        m = C2{bh(shfl_quad(hb(w64.r), 4 * (ks))), bh(shfl_quad(hb(w64.i), 4 * (ks)))}
#define KSTEP(u, v, m) { const C2 A0 = C2{bh(v.z | z), bh(v.w | z)}, A1 = cmulc(A0, m), A2 = cmulc(A1, m), A3 = cmulc(A2, m); \
        mma_f16(acc[0], hb(A0.r), hb(A1.r), hb(A0.i), hb(A1.i), v.x, v.y); \
        mma_f16(acc[2], hb(A0.r), hb(A1.r), hb(A0.i), hb(A1.i), u.x, u.y); \
        mma_f16(acc[4], hb(A0.r), hb(A1.r), hb(A0.i), hb(A1.i), u.z, u.w); \
        mma_f16(acc[1], hb(A2.r), hb(A3.r), hb(A2.i), hb(A3.i), v.x, v.y); \
        mma_f16(acc[3], hb(A2.r), hb(A3.r), hb(A2.i), hb(A3.i), u.x, u.y); }
        uint4 u[2], v[2];
        C2 m[2];
        KLOAD(u[0], v[0], m[0], 0);
#pragma unroll
        for (int ks = 0; ks < 8; ks++) {
            if (ks < 7) { KLOAD(u[(ks + 1) & 1], v[(ks + 1) & 1], m[(ks + 1) & 1], ks + 1); }
            if (UE && ks == UE && w == 3 && !(US5 && s5cta)) fv = ld_flag4(fp);
            KSTEP(u[ks & 1], v[ks & 1], m[ks & 1]);
        }
    }
    TS(40);
    const uint32_t tag = __reduce_max_sync(0xffffffffu, epoch) + 1;
    if (!UE && w == 3) fv = ld_flag4(fp);
    bar_sync(barid, 128);
#define UFETCH() { fence_async_glob(); mbar_expect(ubar, 4096 + 3072); bulk_ld(R + R_LIN, &P.scr->uT[ch * 256], 3072, ubar); \
                   tma2(R + R_U, &P.mu, 0, ch * 64, ubar); TS(41); }
    bool need = w == 3 && !lead && !(US5 && s5cta);
    if (UE && need) {
        if (all4(fv, tag)) { UFETCH(); need = false; }
        else fv = ld_flag4(fp);
    }
    if (PAUSE != 3 && w == 2 && s5cta) mbar_arrive(SB + OFF_BAR + B_K2 * 8);
    if (LEAD == 2 && lead) asm volatile("bar.arrive 14, 512;" ::: "memory");
    {
#pragma unroll
        for (int i = 0; i < 10; i++) sts32(RP + w * 1280 + i * 128 + lane * 4, acc[i >> 1][i & 1]);
        sts128(R + (pD.z >> 16), 0, 0, 0, 0);
        if (tid < 10) sts128(R + (pD.w >> 16), 0, 0, 0, 0);
    }
    bar_sync(barid, 128);
    if (PAUSE == 3 && w == 2 && s5cta) mbar_arrive(SB + OFF_BAR + B_K2 * 8);
    {
        const float F = 2.f * dt * __uint_as_float(cm);
        const uint32_t A0 = pD.x & 0xffff, A1 = pD.x >> 16, B0 = pD.y & 0xffff, B1 = pD.y >> 16, A4 = R + (pD.z & 0xffff);
        const uint32_t Rh = R + (w >= 2 && t >= 2 ? 32 : 256);
        uint32_t v0[3] = {0u, 0u, 0u}, v1[3] = {0u, 0u, 0u};
#pragma unroll
        for (int i = 0; i < 3; i++) {
            const uint32_t pa = RP + (i < 2 ? 2 * w + i : 8 + (w & 1)) * 128 + lane * 4;
            if (i < 2 || w < 2) {
                const float2 q = __half22float2(__hadd2(__hadd2(bh(lds32(pa)), bh(lds32(pa + 1280))), __hadd2(bh(lds32(pa + 2560)), bh(lds32(pa + 3840)))));
                v0[i] = packbf(q.x * F, q.x * F); v1[i] = packbf(q.y * F, q.y * F);
            }
        }
        sts16(R + A0, v0[0]); sts16(R + A1, v0[0]); sts16(R + B0, v1[0]); sts16(R + B1, v1[0]);
        sts16(Rh + A0, v0[1]); sts16(Rh + A1, v0[1]); sts16(Rh + B0, v1[1]); sts16(Rh + B1, v1[1]);
        if (w < 2) { sts16x2(A4, 6, v0[2]); sts16x2(A4 + 32, 6, v1[2]); }
        else if (t < 2) { const uint32_t A = R + (A0 & ~7u); sts64(A + 8, v1[0], v1[0]); sts64(A + 264, v1[1], v1[1]); }
        const uint32_t last = v1[1];
        const uint4 k = lds128(X + 16);
        const uint32_t vs = tid == 63 ? last : tid == 125 ? 0u : packbf(fmaf((float)(int)(k.x + k.y + k.z + k.w), F * (1.f / 1048576.f), dskip), 0.f);
        if (w & 1) sts16x2(R + (pD.w & 0xffff), 6, vs);
    }
    if (need) {
        while (!all4(fv, tag) && ++wd < WD_LIMIT) fv = ld_flag4(fp);
        UFETCH();
    }
    bar_sync(barid, 128);
    if (w == 2 && s5cta) mbar_arrive(SB + OFF_BAR + B_KG * 8);
    TS(42);
    return tag;
}

__device__ __forceinline__ void s4d_conv(const Params& P, int ch, uint32_t R, int cload, int pj, bool s5cta, uint32_t ubar, uint32_t uphase,
                                         int barid, uint32_t tag, int w, int role, uint4 pA, uint4 pB, uint4 pC, uint32_t& wd) {
    const uint32_t z = P.zero;
    {
        {
            const bool r3 = role >= 2;
            const uint32_t one = 0x3f803f80u | z;
            const uint32_t bB[4] = {pB.x, pB.y, pB.z, pB.w};
            const uint32_t kv = __byte_perm(lds32(R + (r3 ? R_FAR + (8 + 3 * FARW + 63) * 4 : R_NB + 544 * 4)), 0, 0x1010);
            const uint32_t e1 = pC.x & kv, e0 = pC.y & kv;
            uint32_t T[2][5][4];
#pragma unroll
            for (int q = 0; q < 2; q++) {
                const uint32_t ta = R + pA.w + q * FARW * 4;
#pragma unroll
                for (int d = 0; d < 5; d++) {
                    T[q][d][0] = lds32(ta + d * 64);
                    T[q][d][1] = d < 4 ? lds32(ta + d * 64 + 32) : mulbf2(T[q][d][0], z);
                    T[q][d][2] = d ? mulbf2(T[q][d - 1][1], one) : mulbf2(T[q][d][0], z);
                    T[q][d][3] = mulbf2(T[q][d][0], one);
                }
            }
            float c[4][4];
#pragma unroll
            for (int d = 0; d < 4; d++) { c[d][0] = c[d][1] = c[d][2] = c[d][3] = 0.f; }
            const float zc[4] = {0.f, 0.f, 0.f, 0.f};
            fence_async_smem();
            bar_sync(barid, 128);
            mbar_wait(ubar, uphase, wd);
            TS(43);
            const uint32_t st = 256u << (role >> 1);
            const uint32_t R1 = R - (st >> 4);
            uint32_t la = pC.z, rho = pC.w;
            uint4 x0 = ldsm4(R + la), x1 = ldsm4(R1 + la);
#define WGEN(more, k8) \
                float d0[4], d1[4], o[4]; \
                mma_bf16_c(d0, bB, x0.x | z, __byte_perm(x1.x, x0.z, pA.z), zc); mma_bf16_c(d1, bB, x0.y | z, __byte_perm(x1.y, x0.w, pA.z), zc); \
                mma_bf16(c[0], x0, e1, e0); \
                if (k8) { mma_bf16_k8(d0, pA.x, pA.y, x1.z); mma_bf16_k8(d1, pA.x, pA.y, x1.w); } \
                if (more) { la += st; x0 = ldsm4(R + la); \
                    if (k8) x1 = ldsm4(R1 + la); else { const uint2 t_ = ldsm2(R1 + la); x1.x = t_.x; x1.y = t_.y; } } \
                const uint32_t p0 = packbf(d0[0], d0[1]), p1 = packbf(d1[0], d1[1]), q0 = packbf(d0[2], d0[3]), q1 = packbf(d1[2], d1[3]);
#define FSTORE() stsm2(R + (rho ^ ((rho >> 3) & 0x70)), packbf(o[0], o[1]), packbf(o[2], o[3])); rho += st;
#pragma unroll 1
            for (int n = r3 ? 0 : role ? 8 - NH0 : NH0; n > 0; n--) {
                WGEN(true, false);
                far_apply(o, c, T, p0, p1, q0, q1);
                FSTORE();
            }
            if (role) {
#pragma unroll
                for (int n = 4; n > 0; n--) {
                    WGEN(n > 1, true);
                    mma_bf16_c(o, T[0][0], p0, p1, c[0]);
#pragma unroll
                    for (int d = 1; d < n; d++) mma_bf16_c(c[d - 1], T[0][d], p0, p1, c[d]);
                    mma_bf16_c(o, T[1][0], q0, q1, o);
#pragma unroll
                    for (int d = 1; d < n; d++) mma_bf16_c(c[d - 1], T[1][d], q0, q1, c[d - 1]);
                    FSTORE();
                }
            }
            if (role == 1) asm volatile("bar.arrive %0, 64;" ::"r"(barid + 5) : "memory");
            if (role == 0) {
                bar_sync(barid + 5, 64);
                rho += (fresh_lane() & 16) * 16;
#pragma unroll
                for (int i = 0; i < 2; i++, rho += 512) {
                    const uint32_t a = R + (rho ^ ((rho >> 3) & 0x70));
                    const uint4 f = ldsm4(a);
                    stsm4(a, addbf2(f.x, packbf(c[2 * i][0], c[2 * i][1])), addbf2(f.y, packbf(c[2 * i][2], c[2 * i][3])),
                          addbf2(f.z, packbf(c[2 * i + 1][0], c[2 * i + 1][1])), addbf2(f.w, packbf(c[2 * i + 1][2], c[2 * i + 1][3])));
                }
            }
            if (s5cta && r3 && cload + role >= 2 * NCE) {
                const int v = cload + role;
                const uint32_t fb = SB + OFF_BAR + (B_FULL2 + v) * 8;
                mbar_wait(SB + OFF_BAR + B_G1 * 8, 0, wd);
                mbar_expect(fb, 16384);
                tma5(SB + (v + 1) * SLOT, &P.mc, (v == 0 ? pj : v - 1 + (v - 1 >= pj)) * 64, pj * 4, 0, fb);
            }
            TS(44);
        }
        {
            float y[32];
            const int lane = fresh_lane();
            const uint32_t ta = R + R_NB + (288 * (w >> 1) + 16 * (w & 1) - 24 + (lane >> 2) - 2 * (lane & 3)) * 4;
            const uint64_t du = mkdesc(R + R_U + 32, 16, 512, 2);
            uint32_t prev = lds32(ta);
#pragma unroll
            for (int b = 0; b < 18 / NB; b++) {
                uint32_t fa[NB][4];
#pragma unroll
                for (int i = 0; i < NB; i++) {
                    fa[i][0] = lds32(ta + (2 * (b * NB + i) + 1) * 32);
                    fa[i][1] = lds32(ta + (2 * (b * NB + i) + 2) * 32);
                }
#pragma unroll
                for (int i = 0; i < NB; i++) { fa[i][3] = fa[i][0] | z; fa[i][2] = prev | z; prev = fa[i][1]; }
                if (b == 0) bar_sync(barid, 128);
                WG_FENCE();
#pragma unroll
                for (int i = 0; i < NB; i++) wgmma_rs64(y, fa[i], du - 2 * (b * NB + i), b | i);
                WG_COMMIT();
                if (NB < 6) WG_WAIT(1); else WG_WAIT(0);
            }
            const int lm = lane >> 3, lr = lane & 7, row = 4 * (lm >> 1) + (lr >> 1);
            const uint32_t a = R + row * 128 + (((4 * (lr & 1) + 2 * (w & 1) + (lm & 1)) ^ row) << 4);
#define PK2(j, h) packbf(y[4 * (j) + 2 * (h)], y[4 * (j) + 2 * (h) + 1])
            if (w >= 2) {
                uint4 f[3];
#pragma unroll
                for (int i = 0; i < 3; i++) {
                    f[i] = ldsm4t(a + R_F2 + i * 1024);
                    if (i) {
                        const uint4 f3 = ldsm4t(a + R_F3 + (i - 1) * 1024);
                        f[i].x = addbf2(f[i].x, f3.x); f[i].y = addbf2(f[i].y, f3.y); f[i].z = addbf2(f[i].z, f3.z); f[i].w = addbf2(f[i].w, f3.w);
                    }
                }
                WG_WAIT(0);
                pin(y);
                stsm2t((a ^ 64) + R_G + 512, PK2(0, 0), PK2(0, 1));
#pragma unroll
                for (int i = 0; i < 3; i++)
                    stsm4t(a + R_G + (i + 1) * 1024, addbf2(PK2(2 * i + 1, 0), f[i].x), addbf2(PK2(2 * i + 1, 1), f[i].y),
                           addbf2(PK2(2 * i + 2, 0), f[i].z), addbf2(PK2(2 * i + 2, 1), f[i].w));
                bar_sync(barid, 128);
            } else {
                WG_WAIT(0);
                pin(y);
                bar_sync(barid, 128);
                TS(45);
                const uint32_t ao = (a ^ ((ch & 2) << 4)) + R_U;
                const uint2 f1 = ldsm2t((a ^ 64) + R_G + 512);
                stsm4t(ao, PK2(0, 0), PK2(0, 1), addbf2(PK2(1, 0), f1.x), addbf2(PK2(1, 1), f1.y));
#pragma unroll
                for (int i = 1; i < 4; i++) {
                    const uint4 f = ldsm4t(a + R_G + i * 1024);
                    stsm4t(ao + i * 1024, addbf2(PK2(2 * i, 0), f.x), addbf2(PK2(2 * i, 1), f.y), addbf2(PK2(2 * i + 1, 0), f.z), addbf2(PK2(2 * i + 1, 1), f.w));
                }
            }
        }
    }
    fence_async_smem();
    bar_sync(barid, 128);
    if (w == 0) {
        bulk_st(&P.scr->aT[ch * 256], R + R_U, 4096);
        if (SDM && s5cta && barid < 5) {
            asm volatile("cp.async.bulk.wait_group.read 0;" ::: "memory");
            __syncwarp();
            mbar_arrive(SB + OFF_BAR + B_SD * 8);
        }
        bulk_wait();
        st_flag(&P.scr->flagA[ch], tag);
    }
    TS(46);
}

__device__ __forceinline__ float2 cexp2(float ar2, float ai, float k) {
    float m = ex2(ar2 * k), a = ai * k;
    return make_float2(m * fcos(a), m * fsin(a));
}
__device__ __forceinline__ float2 cfma(float2 a, float2 b, float2 c) {
    return make_float2(fmaf(a.x, b.x, fmaf(-a.y, b.y, c.x)), fmaf(a.x, b.y, fmaf(a.y, b.x, c.y)));
}

template <bool MULTI>
__global__ void __launch_bounds__(NTHREADS, 1) fused_kernel(const __grid_constant__ Params P) {
    constexpr uint32_t sb = SB;
    constexpr uint32_t bar = sb + OFF_BAR;
    const int bq = (int)blockIdx.x - MAPOFF;
    const bool sp = !MULTI && MAP && (bq < 0 || bq >= 128 || (bq & 7) == 7);
    const int cta = MULTI || !MAP ? (int)blockIdx.x - P.nextra : sp ? -1 : bq - (bq >> 3);
    constexpr int nx = D_ - NS5 * 3;
    int grp = MULTI || !MAP ? (int)blockIdx.x : bq < 0 ? 16 + (int)blockIdx.x : bq >= 128 ? (int)blockIdx.x - 112 : bq >> 3;
    int ch0 = cta < 0 ? grp * 5 : nx - 2 + cta * 3;
    uint32_t wd = 0, round = 0, second = 0;
    TS(threadIdx.x < 32 ? 0 : 63);
    if (threadIdx.x >= 608) TSG(61);
    if (XPF && cta >= 0 && threadIdx.x < 128) asm volatile("prefetch.global.L2 [%0];" ::"l"(P.X + cta * 16384 + threadIdx.x * 128));
#pragma unroll 1
  while (true) {
    uint32_t tx;
    asm volatile("mov.u32 %0, %%tid.x;" : "=r"(tx));
    uint32_t lar2 = 0, aim2 = 0, cr2 = 0, ci2 = 0, sc2 = 0, sd2 = 0;
    if (cta < 0 || tx >= 256) {
        const int o = ch0 * 128 + tx;
        cr2 = ldgv32(P.Cre + o); ci2 = ldgv32(P.Cim + o); lar2 = ldgv32(P.logA + o); aim2 = ldgv32(P.Aim + o);
        sc2 = ldgv16(P.logdtA + (o >> 7)); sd2 = ldgv16(P.DA + (o >> 7));
    }
    const int warp = __shfl_sync(0xffffffffu, tx >> 5, 0), lane = tx & 31, wg = warp >> 2, w = warp & 3;
    const int chunk = (cta * 9363) >> 16, pj = cta - chunk * 7;
    uint32_t* const ep = &P.scr->epoch[blockIdx.x * 24 + warp];

    if (cta >= 0 && wg < 2) {
        constexpr uint32_t xo = sb + OFF_XOWN;
        if (warp == 0) {
            const uint32_t c = 0x100000u - (lane == B_FULL2 ? 9 : lane == B_KG || lane == B_K2 ? 3 : lane >= B_G1 && lane < B_KG ? 2 : 1);
            sts64(bar + lane * 8, lane < B_CNT ? c << 1 : 0, c << 11);
            fence_async_smem();
            if (lane < 8) asm volatile("mbarrier.arrive.expect_tx.shared::cta.b64 _, [%0], %1;" ::"r"(bar + lane * 8), "r"(lane >= 6 ? 16384 : lane == 2 ? 32768 + 128 : 32768) : "memory");
            __syncwarp();
            TS(2);
#pragma unroll 1
            for (int s = 0; s < 3; s++) {
                const int kb = (s + (s >= pj)) * 64;
                if (s == (pj < XE ? 0 : XOS + 1)) tma4(xo, &P.mx, pj * 64, chunk * 4, 0, bar + B_XO * 8);
                tma4(sb + (2 * s + 1) * SLOT, &P.mb, kb, 0, pj * 8, bar + (B_FULL1 + s) * 8);
                tma4(sb + (2 * s + 2) * SLOT, &P.mx, kb, chunk * 4, 0, bar + (B_FULL1 + s) * 8);
            }
            bulk_ld(sb + OFF_GW, P.gw + pj * 64, 128, bar + (B_FULL1 + 2) * 8);
            if (chunk < 7)
                asm volatile(EL "cp.async.bulk.prefetch.tensor.4d.L2.global.tile [%0, {%1, %3, %3, %2}];\n}" ::"l"(&P.mb), "r"(chunk * 64), "r"(pj * 8), "r"(0) : "memory");
#pragma unroll
            for (int i = 3; i < 6; i++) asm volatile("bar.arrive %0, 160;" ::"r"(i) : "memory");
            TS(1);
        }
        const int hw = wg, g = lane >> 2, t = lane & 3;
        const int p = pj * 64 + warp * 8 + g;
        const float Lre = bf1(P.Lre + p), Lim = bf1(P.Lim + p), ldt = bf1(P.logdtB + p);
        const uint32_t db2 = ldg32(P.DB + pj * 64 + 16 * w + 2 * g);
        const uint32_t epoch = ld_flag(ep);
        uint2* const myagg = &P.scr->agg[chunk * 448 + p];
        uint32_t* const myflag = &P.scr->flag[cta * 32];
        if (RS) {
            asm volatile("st.relaxed.gpu.global.v2.u32 [%0], {%1,%1};" ::"l"(myagg), "r"(0) : "memory");
            if (warp == 2) st_flag(myflag + lane, 0);
            if (chunk == 0) st_flag(&P.scr->flagA[p], 0);
            uint32_t c_; asm volatile("mov.u32 %0, %%clock;" : "=r"(c_)::"memory");
        } else {
            *myagg = make_uint2(0u, 0u);
            if (warp == 2) myflag[lane] = 0;
            if (chunk == 0) P.scr->flagA[p] = 0;
        }
        const float dt = bfround(ex2(ldt * LOG2E));
        const float ar2 = Lre * dt * LOG2E, ai = Lim * dt * P.sgnB;
        const float2 lam = cexp2(ar2, ai, 1.f), l16 = cexp2(ar2, ai, 16.f);
        uint32_t m0, m1, m2, m3;
        {
            const float inv = 2.f * frcp(Lre * Lre + Lim * Lim), nr = lam.x - 1.f, li = lam.y * P.sgnB;
            const float sr = (nr * Lre + li * Lim) * inv, ns = (nr * Lim - li * Lre) * inv;
            const bool sw = P.sgnB < 0.f;
            const float a0 = sw ? ns : sr, a1 = sw ? sr : ns;
            m0 = packbf(a0, a0); m1 = packbf(a1, a1); m2 = packbf(a1 * P.sgnB, a1 * P.sgnB); m3 = packbf(a0 * -P.sgnB, a0 * -P.sgnB);
        }
        bar_sync(0, 256);
        const uint32_t tag = epoch + 1, tag4 = (epoch & 7u) | 8u;
        float acc[64];
#define STAGE1(s, bs, xs) { mbar_wait(bar + (B_FULL1 + (s)) * 8, 0, wd); TS(30 + (s)); WG_FENCE(); \
        const uint64_t dx = desc(0x10040 + P.zs[(s) / 3], HI128), da = dx + hw * 512; \
        _Pragma("unroll") for (int k = 0; k < 4; k++) wgmma_n128(acc, da + ((bs) * 1024 + 2 * k), dx + ((xs) * 1024 + 2 * k), (s) | k); \
        WG_COMMIT(); }
        if (!TB || hw) {
            mbar_wait(bar + B_XO * 8, 0, wd);
#pragma unroll 1
            for (int q = TB ? w : warp; q < 8; q += TB ? 4 : 8) {
                const uint32_t row = 2 * g + (t >> 1), sa = sb + q * 2048 + row * 128 + (((4 * (t & 1)) ^ (row & 7)) << 4);
                uint4 v[4];
#pragma unroll
                for (int h = 0; h < 4; h++) v[h] = ldsm4t(xo + (32 * h + lane) * 128 + ((q ^ (lane & 7)) << 4));
#pragma unroll
                for (int h = 0; h < 4; h++) sts128(sa ^ (h << 4), v[h].x, v[h].y, v[h].z, v[h].w);
                fence_async_smem();
                __syncwarp();
                asm volatile(EL "cp.async.bulk.tensor.3d.global.shared::cta.bulk_group [%0, {%4, %2, %3}], [%1];\n}\ncp.async.bulk.commit_group;"
                             ::"l"(&P.ms), "r"(sb + q * 2048), "r"(2 * chunk), "r"(pj * 64 + q * 8), "r"(0) : "memory");
            }
            TS(58);
        }
#define REL(s) if (SKEW == (s) && !hw) asm volatile("bar.arrive 12, 256;" ::: "memory")
#define REFILL(n) { const int kb = ((n) + ((n) >= pj)) * 64; \
        tma4(sb + (2 * (n) - 5) * SLOT, &P.mb, kb, 0, pj * 8, bar + (B_FULL1 + (n)) * 8); \
        tma4(sb + (2 * (n) - 4) * SLOT, &P.mx, kb, chunk * 4, 0, bar + (B_FULL1 + (n)) * 8); }
        STAGE1(0, 1, 2);
        if (FS) STAGE1(1, 3, 4);
        bulk_wait();
        st_flag(myflag + warp, tag);
        TS(4);
        if (!FS) STAGE1(1, 3, 4);
        if (ERF) { WG_WAIT(1); if (w == 1 && second_arrival(bar + (B_CNT + 5) * 8)) REFILL(3); }
        STAGE1(2, 5, 6);
        WG_WAIT(0);
        bar_sync(0, 256);
        if (warp == 0) {
#pragma unroll 1
            for (int n = 3 + ERF; n < 6; n++) REFILL(n);
            tma4(sb, &P.mb, pj * 64, 0, pj * 8, bar + (B_FULL1 + 6) * 8);
        }
        {
            float gd[4];
            WG_FENCE();
#pragma unroll
            for (int k = 0; k < 4; k++) wgmma_n8(gd, desc(0x10040 + 7 * 1024 + hw * 512, HI128) + 2 * k, mkdesc(sb + OFF_GW, 16, 128, 0) + 2 * k, k);
            WG_COMMIT();
            WG_WAIT(0);
            pin(gd);
            if (t == 0) {
                uint32_t* gp = &P.scr->gpart[cta * 128 + 32 * (g >> 1) + 4 * warp + (g & 1)];
                st_flag(gp, (__float_as_uint(gd[0]) & ~15u) | tag4);
                st_flag(gp + 2, (__float_as_uint(gd[2]) & ~15u) | tag4);
            }
        }
        if (w == 2) asm volatile(EL "cp.async.bulk.prefetch.L2.global [%0], %1;\n}" ::"l"((&P.Cr)[hw] + cta * 3584), "r"(3584) : "memory");
        if (US5 && warp >= 5) {
            const int ch = nx + cta * 3 + warp - 5;
            const uint32_t* fp = &P.scr->flag[((lane >> 1) * 7 + (ch >> 6)) * 32 + (lane & 1) * 4];
            while (!all4(ld_flag4(fp), tag) && ++wd < WD_LIMIT) {}
            fence_async_glob();
            const uint32_t R = sb + (warp == 5 ? 9 : warp == 6 ? 10 : 13) * SLOT, ub = bar + (B_U + warp - 3) * 8;
            mbar_wait(bar + B_K2 * 8, 0, wd);
            mbar_expect(ub, 4096 + 3072);
            bulk_ld(R + R_LIN, &P.scr->uT[ch * 256], 3072, ub);
            tma2(R + R_U, &P.mu, 0, ch * 64, ub);
            TS(41);
        }
        if (PAUSE) mbar_wait(bar + (PAUSE == 2 || (PAUSE == 4 && hw) ? B_KG : B_K2) * 8, 0, wd);
        if (SKEW && hw) bar_sync(12, 256);
        STAGE1(3, 1, 2);
        REL(3);
#define CLOAD(v) { mbar_expect(bar + (B_FULL2 + (v)) * 8, 16384); \
        tma5(sb + ((v) + 1) * SLOT, &P.mc, ((v) == 0 ? pj : (v) - 1 + ((v) - 1 >= pj)) * 64, pj * 4, 0, bar + (B_FULL2 + (v)) * 8); }
        STAGE1(4, 3, 4);
        REL(4);
        if (NCE > 0) { WG_WAIT(1); if (w == 1 && second_arrival(bar + (B_CNT + 2) * 8)) { CLOAD(0); CLOAD(1); } }
        STAGE1(5, 5, 6);
        REL(5);
        if (NCE > 1) { WG_WAIT(1); if (w == 1 && second_arrival(bar + (B_CNT + 3) * 8)) { CLOAD(2); CLOAD(3); } }
        STAGE1(6, 0, 7);
        REL(6);
        if (NCE > 2) { WG_WAIT(1); if (w == 1 && second_arrival(bar + (B_CNT + 4) * 8)) { CLOAD(4); CLOAD(5); } }
        st_flag(ep, tag);
        WG_WAIT(0);
        pin(acc);
        if (w == 0) mbar_arrive(bar + B_G1 * 8);
        TS(12);
#define AX(i) acc[4 * ((i) >> 1) + ((i) & 1)]
#define AY(i) acc[4 * ((i) >> 1) + 2 + ((i) & 1)]
        const float2 zero2 = make_float2(0.f, 0.f);
        float2 e = make_float2(AX(0), AY(0)), e2 = make_float2(AX(16), AY(16));
#pragma unroll
        for (int i = 1; i < 16; i++) { e = cfma(lam, e, make_float2(AX(i), AY(i))); e2 = cfma(lam, e2, make_float2(AX(16 + i), AY(16 + i))); }
        const float2 e16 = e;
        e = cfma(l16, e, e2);
        {
            const float2 l32 = cfma(l16, l16, zero2), l64 = cfma(l32, l32, zero2);
            float2 o = make_float2(__shfl_up_sync(0xffffffffu, e.x, 1, 4), __shfl_up_sync(0xffffffffu, e.y, 1, 4));
            if (t >= 1) e = cfma(l32, o, e);
            o = make_float2(__shfl_up_sync(0xffffffffu, e.x, 2, 4), __shfl_up_sync(0xffffffffu, e.y, 2, 4));
            if (t >= 2) e = cfma(l64, o, e);
        }
        if (t == 3)
            asm volatile("st.relaxed.gpu.global.v2.u32 [%0], {%1,%2};" ::"l"(myagg), "r"((__float_as_uint(e.x) & ~15u) | tag4), "r"(__float_as_uint(e.y)) : "memory");
        TS(14);
        float2 h = make_float2(__shfl_up_sync(0xffffffffu, e.x, 1, 4), __shfl_up_sync(0xffffffffu, e.y, 1, 4));
        if (t == 0) h = zero2;
        {
            const float2 l512 = cexp2(ar2, ai, 512.f), l128t = cexp2(ar2, ai, 128.f * t), l32t = cexp2(ar2, ai, 32.f * t);
            uint2 v[4];
#pragma unroll
            for (int i = 0; i < 4; i++) v[i] = make_uint2(tag4, 0u);
            const uint2* src = myagg - (t + 1) * 448;
            bool ok;
            do {
                asm volatile("{\n.reg .pred p0, p1, p2, p3;\n"
                             "setp.gt.s32 p0, %9, 0;\nsetp.gt.s32 p1, %9, 4;\nsetp.gt.s32 p2, %9, 8;\nsetp.gt.s32 p3, %9, 12;\n"
                             "@p0 ld.relaxed.gpu.global.v2.u32 {%0,%1}, [%8];\n"
                             "@p1 ld.relaxed.gpu.global.v2.u32 {%2,%3}, [%8+-14336];\n"
                             "@p2 ld.relaxed.gpu.global.v2.u32 {%4,%5}, [%8+-28672];\n"
                             "@p3 ld.relaxed.gpu.global.v2.u32 {%6,%7}, [%8+-43008];\n}"
                             : "+r"(v[0].x), "+r"(v[0].y), "+r"(v[1].x), "+r"(v[1].y), "+r"(v[2].x), "+r"(v[2].y), "+r"(v[3].x), "+r"(v[3].y)
                             : "l"(src), "r"(chunk - t) : "memory");
                ok = __all_sync(0xffffffffu, (((v[0].x ^ tag4) | (v[1].x ^ tag4) | (v[2].x ^ tag4) | (v[3].x ^ tag4)) & 15u) == 0);
            } while (!ok && ++wd < WD_LIMIT);
            float2 c = make_float2(__uint_as_float(v[3].x), __uint_as_float(v[3].y));
#pragma unroll
            for (int i = 2; i >= 0; i--) c = cfma(l512, c, make_float2(__uint_as_float(v[i].x), __uint_as_float(v[i].y)));
            c = cfma(l128t, c, zero2);
            c.x += __shfl_xor_sync(0xffffffffu, c.x, 1); c.y += __shfl_xor_sync(0xffffffffu, c.y, 1);
            c.x += __shfl_xor_sync(0xffffffffu, c.x, 2); c.y += __shfl_xor_sync(0xffffffffu, c.y, 2);
            h = cfma(l32t, c, h);
        }
        TS(16);
        mbar_wait(bar + B_KG * 8, 0, wd);
        {
            const uint32_t hb = sb + 11 * SLOT + warp * 4096;
            const uint32_t ha = hb + (lane >> 4) * (HH ? 1024 : 2048) + (lane & 15) * 16;
#pragma unroll
            for (int j = 0; j < 8; j++) {
                const float2 h0 = cfma(lam, h, make_float2(AX(4 * j), AY(4 * j)));
                const float2 h1 = cfma(lam, h0, make_float2(AX(4 * j + 1), AY(4 * j + 1)));
                const float2 h2 = cfma(lam, h1, make_float2(AX(4 * j + 2), AY(4 * j + 2)));
                h = cfma(lam, h2, make_float2(AX(4 * j + 3), AY(4 * j + 3)));
                const uint32_t x0 = packbf(h0.x, h1.x), x1 = packbf(h2.x, h.x), y0 = packbf(h0.y, h1.y), y1 = packbf(h2.y, h.y);
                if (HH && j == 4) { fence_async_smem(); __syncwarp(); bulk_st(&P.scr->h[(cta * 8 + warp) * 256], hb, 2048); }
                stsm4(ha + (j & (HH ? 3 : 7)) * 256 + (HH ? (j >> 2) * 2048 : 0), fmabf2(m0, x0, mulbf2n(m1, y0)), fmabf2(m0, x1, mulbf2n(m1, y1)), fmabf2(m2, x0, mulbf2n(m3, y0)), fmabf2(m2, x1, mulbf2n(m3, y1)));
            }
            fence_async_smem();
            __syncwarp();
            TS(18);
            if (HH && !DUAL) bulk_st(&P.scr->h[(cta * 8 + warp) * 256 + 128], hb + 2048, 2048);
            else bulk_st(&P.scr->h[(cta * 8 + warp) * 256], hb, 4096);
        }
        if (OPT & 2) { bulk_wait(); st_flag(myflag + 8 + warp, tag); TS(20); }
        uint32_t ud[2][8];
        {
            const uint32_t xa = xo + (64 * hw + 2 * t) * 128 + (g & 3) * 4 + (((2 * w + (g >> 2)) ^ (2 * t)) << 4);
#pragma unroll
            for (int j = 0; j < 8; j++) {
                const uint32_t v0 = mulbf2n(lds32(xa + j * 1024), db2), v1 = mulbf2n(lds32((xa ^ 16) + j * 1024 + 128), db2);
                ud[0][j] = __byte_perm(v0, v1, 0x5410); ud[1][j] = __byte_perm(v0, v1, 0x7632);
            }
        }
        __syncwarp();
        mbar_arrive(bar + B_FULL2 * 8);
        if (!(OPT & 2)) { bulk_wait(); st_flag(myflag + 8 + warp, tag); TS(20); }
        float o[32];
        uint4 g2[2], o2[2];
        {
            const uint4* hsrc = &P.scr->h[chunk * 14336];
#define TILE2(co, ho, sd, zz) { WG_FENCE(); const uint64_t a_ = desc(0x10040 + (co) + P.swapC + (zz), HI128), b_ = desc(0x10240 + (co) - P.swapC + (zz), HI128), \
            h_ = desc(0x1000040 + (ho) + hw * (HH ? 128 : 64) + (zz), 8); \
            _Pragma("unroll") for (int k = 0; k < 8; k++) \
                wgmma_n64_tb(o, ((k & 2) ? b_ : a_) + ((k >> 2) * 4 + (k & 1) * 2), h_ + ((k >> 2) * 1024 + (k & 1) * 512 + (k & 2) * (HH ? 32 : 64)), (sd) | k); \
            WG_COMMIT(); }
            if (!(OPT & 4)) { mbar_wait(bar + B_FULL2 * 8, 0, wd); TS(47); TILE2(1024, 11 * 1024, 0, P.zs[3]); }
#define HLOAD(n, slot) { mbar_expect(bar + (B_FULL2 + (n)) * 8, 32768); \
            bulk_ld(sb + (slot) * SLOT, hsrc + ((n) - 1 + ((n) - 1 >= pj)) * 2048, 32768, bar + (B_FULL2 + (n)) * 8); }
            if (hw) {
                const uint32_t* gp = &P.scr->gpart[chunk * 896 + w * 32 + lane];
                float zs; bool ok;
                do {
                    uint32_t bad = 0;
                    zs = 0.f;
#pragma unroll
                    for (int i = 0; i < 7; i++) { const uint32_t x = ld_flag(gp + i * 128); bad |= x ^ tag4; zs += __uint_as_float(x); }
                    ok = __all_sync(0xffffffffu, (bad & 15u) == 0);
                } while (!ok && ++wd < WD_LIMIT);
                const float gt = frcp(1.f + ex2(-LOG2E * zs));
                const uint32_t ga = sb + OFF_G + w * 80 + lane * 2, pk = packbf(gt, 1.f - gt);
                sts16(ga, pk); sts16(ga + 320, pk >> 16);
            } else if (w == 1) {
                const uint32_t* fp = &P.scr->flag[(chunk * 7 + (lane < 14 ? lane >> 1 : 0)) * 32 + 8 + (lane & 1) * 4];
                bool mine;
                do {
                    const uint4 f = ld_flag4(fp);
                    mine = ((f.x ^ tag) | (f.y ^ tag) | (f.z ^ tag) | (f.w ^ tag)) == 0;
                } while (!__all_sync(0xffffffffu, mine || (F1 && (lane >> 1) != (pj == 0))) && ++wd < WD_LIMIT);
                TS(3);
                fence_async_glob();
                if (OPT & 4) mbar_wait(bar + B_FULL2 * 8, 0, wd);
                HLOAD(1, 7);
                if (F1 && !__all_sync(0xffffffffu, mine)) {
                    while (!all4(ld_flag4(fp), tag) && ++wd < WD_LIMIT) {}
                    fence_async_glob();
                }
            }
            if (OPT & 4) { if (OPT & 16) bar_sync(0, 256); mbar_wait(bar + B_FULL2 * 8, 0, wd); TS(47); TILE2(1024, 11 * 1024, 0, P.zs[3]); }
            WG_WAIT(0);
            bar_sync(0, 256);
            if (warp == 1) { HLOAD(2, 11); HLOAD(3, 0); if (SDM >= 2) mbar_arrive(bar + B_HF * 8); }
            if (warp == 5 && SDM < 3) { mbar_wait(bar + B_SD * 8, 0, wd); if (SDM < 2) HLOAD(4, 9); }
#pragma unroll
            for (int i = 0; i < 2; i++) {
                const uint32_t ga = sb + OFF_G + t * 80 + hw * 32 + i * 16;
                g2[i] = lds128(ga); o2[i] = lds128(ga + 320);
            }
#define STAGE2(v, cslot, hslot) { mbar_wait(bar + (B_FULL2 + (v)) * 8, 0, wd); TS(47 + (v)); TILE2((cslot) * 1024, (hslot) * 1024, 1, P.zs[(v) / 5]); }
            STAGE2(1, 2, 7);
            STAGE2(2, 3, 11);
            WG_WAIT(1);
            if (w == 1 && second_arrival(bar + B_CNT * 8)) {
                HLOAD(5, 7);
                mbar_expect(bar + (B_FULL2 + 6) * 8, 16384);
                tma5(sb + 2 * SLOT, &P.mc, (pj == 6 ? 5 : 6) * 64, pj * 4, 0, bar + (B_FULL2 + 6) * 8);
            }
            STAGE2(3, 4, 0);
            WG_WAIT(1);
            if (w == 1 && second_arrival(bar + (B_CNT + 1) * 8)) HLOAD(6, 11);
            if (SKEW2 == 4 && hw) bar_sync(13, 256);
            STAGE2(4, 5, 9);
            if (SKEW2 == 5 && hw) bar_sync(13, 256);
            STAGE2(5, 6, 7);
            STAGE2(6, 2, 11);
            if (SKEW2 && !hw) asm volatile("bar.arrive 13, 256;" ::: "memory");
        }
        TS(28);
        {
            const uint32_t gg[8] = {g2[0].x, g2[0].y, g2[0].z, g2[0].w, g2[1].x, g2[1].y, g2[1].z, g2[1].w};
            const uint32_t oo[8] = {o2[0].x, o2[0].y, o2[0].z, o2[0].w, o2[1].x, o2[1].y, o2[1].z, o2[1].w};
            const int n7 = (2 * chunk + (t >> 1)) & 7, q = 4 * (t & 1) + 2 * hw;
            float* op = P.out + (chunk * 128 + 32 * t + 16 * hw) * D_ + pj * 64 + 16 * w + 2 * g;
            const uint32_t aa = sb + 13 * SLOT + (16 * w + 2 * g) * 256 + (t >> 1) * 128 + ((q ^ n7 ^ (2 * (g & 1))) << 4);
            mbar_wait(bar + B_GA * 8, 0, wd);
#pragma unroll
            for (int i = 0; i < 4; i++) {
                const uint4 a = lds128((aa ^ ((i & 1) << 4)) + (i >> 1) * 256);
                const uint32_t av[4] = {a.x, a.y, a.z, a.w};
#pragma unroll
                for (int k = 0; k < 4; k++) ud[i >> 1][4 * (i & 1) + k] = fmabf2(oo[4 * (i & 1) + k], ud[i >> 1][4 * (i & 1) + k], mulbf2n(gg[4 * (i & 1) + k], av[k]));
            }
            WG_WAIT(0);
            pin(o);
            TS(24);
#pragma unroll
            for (int i = 0; i < 16; i++) {
                const float om = (i & 1) ? bfhi(oo[i >> 1]) : bflo(oo[i >> 1]);
                const float x0 = (i & 1) ? bfhi(ud[0][i >> 1]) : bflo(ud[0][i >> 1]), x1 = (i & 1) ? bfhi(ud[1][i >> 1]) : bflo(ud[1][i >> 1]);
                *reinterpret_cast<float2*>(op + i * D_) = make_float2(fmaf(om, o[4 * (i >> 1) + (i & 1)], x0), fmaf(om, o[4 * (i >> 1) + 2 + (i & 1)], x1));
            }
            TS(26);
        }
        break;
    } else {
        const bool sixth = cta < 0 && grp < nx - 100;
        const uint32_t Rm = sb + (wg + 2) * S4D_SZ + (wg == 3 ? 0 : SLOT), um = bar + (B_U + wg) * 8;
        if (cta < 0 && round == 0 && w == 3) { mbar_init(second ? bar : um, 1); fence_async_smem(); }
        if (wg == 2) asm volatile(EL "prefetch.tensormap [%0];\n}" ::"l"(&P.mc + w) : "memory");
        const uint32_t epoch = ld_flag(ep + (lane & P.zero));
        const int role = (w + ((ROT >> (2 * wg)) & 3)) & 3;
        uint4 pA = ldg128(P.pat->v[role][0][lane]), pB = ldg128(P.pat->v[role][1][lane]), pC = ldg128(P.pat->v[role][2][lane]);
        if (sixth && wg == 1)
            asm volatile(EL "cp.async.bulk.prefetch.L2.global [%0], 512;\n}" ::"l"((&P.logA)[w] + (100 + grp) * 128) : "memory");
        if (LEAD && sixth && wg >= 2) bar_sync(14, 512);
        TS(39);
        const uint32_t tag = s4d_kgen(P, ch0 + wg, second ? sb : sb + (wg + 2) * S4D_SZ, second ? sb : Rm, cta >= 0, second ? bar : um, 1 + wg,
                                      epoch, lar2, aim2, cr2, ci2, bflo(sc2), bflo(sd2), w, tx & 127, sixth && wg == 0 && !second, wd);
        if (sixth && wg == 0) {
            if (!second) { second = 1; ch0 = 100 + grp; continue; }
            asm volatile("bar.arrive 12, 256;" ::: "memory");
            second = 0; ch0 = grp * 5;
            if (w == 3) {
                const int l1 = fresh_lane();
                const uint32_t* fp = &P.scr->flag[(l1 >> 1) * 7 * 32 + (l1 & 1) * 4];
                while (!all4(ld_flag4(fp), tag) && ++wd < WD_LIMIT) {}
                fence_async_glob();
                mbar_expect(um, 4096 + 3072);
                bulk_ld(Rm + R_LIN, &P.scr->uT[ch0 * 256], 3072, um);
                tma2(Rm + R_U, &P.mu, 0, ch0 * 64, um);
            }
        }
        int ch = ch0 + wg;
        uint32_t R = Rm, ub = um;
#pragma unroll 1
        while (true) {
            s4d_conv(P, ch, R, 2 * wg - 6, pj, cta >= 0, ub, round & 1, 1 + wg, tag, w, role, pA, pB, pC, wd);
            if (!(sixth && wg == 1) || R == sb) break;
            const int l1 = fresh_lane();
            pA = ldg128(P.pat->v[role][0][l1]); pB = ldg128(P.pat->v[role][1][l1]); pC = ldg128(P.pat->v[role][2][l1]);
            bar_sync(12, 256);
            ch = 100 + grp; R = sb; ub = bar;
        }
        if (MULTI && cta < 0) {
            round++; grp += P.nextra; ch0 = grp * 5;
            if (grp < 20) { bar_sync(13, NTHREADS); continue; }
        }
        st_flag(ep, tag);
        if (!SDM && cta >= 0 && w == 0 && wg < 4) mbar_arrive(bar + B_SD * 8);
        if (SDM >= 2 && cta >= 0 && warp == 9) {
            mbar_wait(bar + B_SD * 8, 0, wd);
            mbar_wait(bar + B_HF * 8, 0, wd);
            mbar_expect(bar + (B_FULL2 + 4) * 8, 32768);
            bulk_ld(sb + 9 * SLOT, &P.scr->h[chunk * 14336 + (3 + (3 >= pj)) * 2048], 32768, bar + (B_FULL2 + 4) * 8);
        }
        if (cta >= 0 && warp == 16) {
            asm volatile(EL "prefetch.tensormap [%0];\n}" ::"l"(&P.ma) : "memory");
            bool ok;
            do {
                const uint2 v = ld_flag2(&P.scr->flagA[pj * 64 + 2 * fresh_lane()]);
                ok = __all_sync(0xffffffffu, v.x == tag && v.y == tag);
            } while (!ok && ++wd < WD_LIMIT);
            TS(8);
            fence_async_glob();
            mbar_expect(bar + B_GA * 8, 16384);
            tma2(sb + 13 * SLOT, &P.ma, chunk * 128, pj * 64, bar + B_GA * 8);
        }
        break;
    }
  }
    TSDUMP();
}

typedef CUresult (*EncodeFn)(CUtensorMap*, CUtensorMapDataType, cuuint32_t, void*, const cuuint64_t*, const cuuint64_t*,
                             const cuuint32_t*, const cuuint32_t*, CUtensorMapInterleave, CUtensorMapSwizzle,
                             CUtensorMapL2promotion, CUtensorMapFloatOOBfill);

}

extern "C" void kernel_launch(void* const* d_in, const int* in_sizes, int n_in, void* d_out, int out_size) {
    (void)in_sizes; (void)n_in; (void)out_size;
    static EncodeFn enc = nullptr;
    static int nsm = 0;
    static char* scr = nullptr;
    static void* pat = nullptr;
    if (!enc) {
        void* fn = nullptr;
        cudaDriverEntryPointQueryResult qr;
        cudaGetDriverEntryPoint("cuTensorMapEncodeTiled", &fn, cudaEnableDefault, &qr);
        enc = (EncodeFn)fn;
        cudaGetSymbolAddress((void**)&scr, g_scr);
        cudaGetSymbolAddress(&pat, g_pat);
        cudaDeviceGetAttribute(&nsm, cudaDevAttrMultiProcessorCount, 0);
        cudaFuncSetAttribute(fused_kernel<false>, cudaFuncAttributeMaxDynamicSharedMemorySize, SMEM_BYTES);
        cudaFuncSetAttribute(fused_kernel<true>, cudaFuncAttributeMaxDynamicSharedMemorySize, SMEM_BYTES);
    }
    Params P;
    const cuuint32_t es[5] = {1, 1, 1, 1, 1};
    const cuuint64_t RB = D_ * 2;
    {
        cuuint64_t gd[4] = {D_, 2, 64, 16}, gs[3] = {RB, 32 * RB, 2 * RB};
        cuuint32_t bx[4] = {64, 2, 4, 16};
        enc(&P.mx, CU_TENSOR_MAP_DATA_TYPE_BFLOAT16, 4, d_in[0], gd, gs, bx, es, CU_TENSOR_MAP_INTERLEAVE_NONE,
            CU_TENSOR_MAP_SWIZZLE_128B, CU_TENSOR_MAP_L2_PROMOTION_L2_128B, CU_TENSOR_MAP_FLOAT_OOB_FILL_NONE);
    }
    {
        char *a = (char*)d_in[10], *b = (char*)d_in[11];
        const bool swapB = b < a;
        P.sgnB = swapB ? -1.f : 1.f;
        cuuint64_t gd[4] = {D_, 8, 2, 56}, gs[3] = {RB, (cuuint64_t)(swapB ? a - b : b - a), 8 * RB};
        cuuint32_t bx[4] = {64, 8, 2, 8};
        enc(&P.mb, CU_TENSOR_MAP_DATA_TYPE_BFLOAT16, 4, swapB ? b : a, gd, gs, bx, es, CU_TENSOR_MAP_INTERLEAVE_NONE,
            CU_TENSOR_MAP_SWIZZLE_128B, CU_TENSOR_MAP_L2_PROMOTION_L2_128B, CU_TENSOR_MAP_FLOAT_OOB_FILL_NONE);
    }
    {
        char *a = (char*)d_in[12], *b = (char*)d_in[13];
        P.swapC = b < a ? 512 : 0;
        cuuint64_t gd[5] = {D_, 8, 2, 28, 2}, gs[4] = {2 * RB, RB, 16 * RB, (cuuint64_t)(P.swapC ? a - b : b - a)};
        cuuint32_t bx[5] = {64, 8, 2, 4, 2};
        enc(&P.mc, CU_TENSOR_MAP_DATA_TYPE_BFLOAT16, 5, P.swapC ? b : a, gd, gs, bx, es, CU_TENSOR_MAP_INTERLEAVE_NONE,
            CU_TENSOR_MAP_SWIZZLE_128B, CU_TENSOR_MAP_L2_PROMOTION_L2_128B, CU_TENSOR_MAP_FLOAT_OOB_FILL_NONE);
        P.Cr = a; P.Ci = b;
    }
    {
        cuuint64_t gd[2] = {L_, D_}, gs[1] = {L_ * 2};
        cuuint32_t bx[2] = {128, 64};
        enc(&P.ma, CU_TENSOR_MAP_DATA_TYPE_BFLOAT16, 2, scr + offsetof(Scratch, aT), gd, gs, bx, es, CU_TENSOR_MAP_INTERLEAVE_NONE,
            CU_TENSOR_MAP_SWIZZLE_NONE, CU_TENSOR_MAP_L2_PROMOTION_L2_128B, CU_TENSOR_MAP_FLOAT_OOB_FILL_NONE);
    }
    {
        cuuint64_t gd[2] = {32, D_ * 64}, gs[1] = {64};
        cuuint32_t bx[2] = {32, 64};
        enc(&P.mu, CU_TENSOR_MAP_DATA_TYPE_BFLOAT16, 2, scr + offsetof(Scratch, uT), gd, gs, bx, es, CU_TENSOR_MAP_INTERLEAVE_NONE,
            CU_TENSOR_MAP_SWIZZLE_64B, CU_TENSOR_MAP_L2_PROMOTION_L2_128B, CU_TENSOR_MAP_FLOAT_OOB_FILL_NONE);
    }
    {
        cuuint64_t gd[3] = {64, 32, D_}, gs[2] = {128, L_ * 2};
        cuuint32_t bx[3] = {64, 2, 8};
        enc(&P.ms, CU_TENSOR_MAP_DATA_TYPE_BFLOAT16, 3, scr + offsetof(Scratch, uT), gd, gs, bx, es, CU_TENSOR_MAP_INTERLEAVE_NONE,
            CU_TENSOR_MAP_SWIZZLE_128B, CU_TENSOR_MAP_L2_PROMOTION_NONE, CU_TENSOR_MAP_FLOAT_OOB_FILL_NONE);
    }
    P.zero = 0; P.zs[0] = P.zs[1] = P.zs[2] = P.zs[3] = 0;
    P.scr = (Scratch*)scr; P.pat = (const PatTab*)pat;
    P.logA = (const uint32_t*)d_in[1]; P.Aim = (const uint32_t*)d_in[2];
    P.Cre = (const uint32_t*)d_in[3]; P.Cim = (const uint32_t*)d_in[4];
    P.logdtA = (const uint16_t*)d_in[5]; P.DA = (const uint16_t*)d_in[6];
    P.Lre = (const uint16_t*)d_in[8]; P.Lim = (const uint16_t*)d_in[9];
    P.logdtB = (const uint16_t*)d_in[14]; P.DB = (const uint16_t*)d_in[15]; P.gw = (const uint16_t*)d_in[16];
    P.out = (float*)d_out;
    P.X = (const char*)d_in[0];
    int nextra = nsm - NS5;
    if (nextra > 20) nextra = 20;
    if (nextra < 1) nextra = 1;
    P.nextra = nextra;
    if (nextra == 20) fused_kernel<false><<<NS5 + nextra, NTHREADS, SMEM_BYTES, cudaStreamPerThread>>>(P);
    else fused_kernel<true><<<NS5 + nextra, NTHREADS, SMEM_BYTES, cudaStreamPerThread>>>(P);
}
```
